```python
import torch

def _softmax(x, axis=-1):
    return torch.softmax(x, dim=axis)
def _gelu(x):
    return torch.nn.functional.gelu(x, approximate="tanh")
def _silu(x):
    return torch.nn.functional.silu(x)
def _sigmoid(x):
    return torch.sigmoid(x)
def _layernorm(x, axis=-1, eps=1e-5):
    m = x.mean(dim=axis, keepdim=True)
    v = x.var(dim=axis, keepdim=True, unbiased=False)
    return (x - m) / torch.sqrt(v + eps)
def _scatter_add(tgt, idx, src, axis=0):
    return tgt.clone().index_add_(axis, idx, src)
def _segment_sum(src, seg, n):
    out = torch.zeros((n,) + src.shape[1:], dtype=src.dtype)
    return out.index_add_(0, seg, src)
def _pad(x, pw):
    flat = tuple(v for pair in reversed(pw) for v in pair)
    return torch.nn.functional.pad(x, flat)

kernel_name = 'standalone__global_local_windowed_global_tokens__prompt'

def setup_inputs():

    _w = (lambda a: (lambda t: t.to(torch.bfloat16) if t.is_floating_point() else t)(torch.as_tensor(a)))
    B, H, S, D = 1, 16, 2048, 256
    return {
        "q": _w((lambda *s: torch.randn(*s, dtype=torch.bfloat16) * 0.8)(B, H, S, D)),
        "k": _w((lambda *s: torch.randn(*s, dtype=torch.bfloat16) * 0.8)(B, H, S, D)),
        "v": _w((lambda *s: torch.randn(*s, dtype=torch.bfloat16) * 0.05)(B, H, S, D)),
        "window": 32,
        "n_global": 2,
    }

def reference(q, k, v, window, n_global):
    B, H, S, D = q.shape
    scale = D ** -0.5
    scores = torch.einsum("bhqd,bhkd->bhqk", q, k) * scale
    idx = torch.arange(S)
    dist = idx[:, None] - idx[None, :]
    local = (dist <= window) & (dist >= -window)
    is_global_q = (idx < n_global)[:, None]
    is_global_k = (idx < n_global)[None, :]
    mask = local | is_global_q | is_global_k
    scores = torch.where(mask[None, None], scores, -1e9)
    p = _softmax(scores, axis=-1)
    return torch.einsum("bhqk,bhkd->bhqd", p, v)
```

```cpp
#include <cuda_runtime.h>
#include <cuda.h>
#include <cuda_bf16.h>
#include <stdint.h>

#define SCHED 8
#define WIN 3
#define WHI 9
#define TAU 400
#define TOFF -3000
#define PFAST 14
#define TAUF 0
#define DEFER -1
#define STAGE 0
#define POLLWAIT (B_REL + K3)
#define POLLNS 100
#define PVORD 1
#define SPLIT3 1
#define HITSEP 1
#define TL 0
#define WATCHDOG 0

namespace {

constexpr int NH = 16, SEQ = 2048, HD = 256;
constexpr int FAST_W = 32, FAST_G = 2;

constexpr uint32_t base = 1024;
constexpr uint32_t SM_X = 196608;
constexpr uint32_t SM_KG = 212992;
constexpr uint32_t SM_VG = 217088;
constexpr uint32_t SM_GR = 225280;
constexpr uint32_t SM_BAR = SM_GR + 4352;
constexpr int B_FULL = 0, B_REL = 56, B_SF = 72, B_GV = 88, B_GR = 93;
constexpr uint32_t SM_TL = SM_BAR + 96 * 8;
constexpr uint32_t SM_TOTAL = SM_TL + (TL ? 1024 : 0);
constexpr uint32_t bars = base + SM_BAR;
#define TLOG(i)

struct Maps { CUtensorMap k, v, q, v32, k32, o, o62; };

enum { K0, V0, Q0, K1, V1, Q1, K2, V2, Q2, K3, V3, Q3, K4, V4 };
#define ORDER_LIST K0, K1, Q0, V0, V1, K2, Q1, V2, K3, Q2, V3, Q3, K4, V4
#define PREV_LIST -1, -4, -3, -2, -5, Q0, -6, K0, Q1, V0, K1, V1, Q2, K2
__host__ __device__ constexpr int slot_of(int b) {
    constexpr int prev[14] = {PREV_LIST};
    while (prev[b] >= 0) b = prev[b];
    return -1 - prev[b];
}
__host__ __device__ constexpr uint64_t nib_tab(int what) {
    constexpr int ord[14] = {ORDER_LIST};
    constexpr int prev[14] = {PREV_LIST};
    uint64_t r = 0;
    for (int i = 0; i < 14; i++) {
        const int x = what == 0 ? ord[i] : what == 1 ? slot_of(ord[i]) : what == 2 ? (prev[ord[i]] & 15) : slot_of(i);
        r |= (uint64_t)x << (4 * i);
    }
    return r;
}
constexpr uint64_t TAB_ORD = nib_tab(0), TAB_PSLOT = nib_tab(1), TAB_PREV = nib_tab(2), TAB_SLOT = nib_tab(3);
constexpr uint32_t Q3_HI_SHIFT = (uint32_t)(slot_of(K4) - slot_of(Q3)) * 32768u;
__host__ __device__ constexpr uint32_t nib(uint64_t tab, int i) { return (uint32_t)(tab >> (4 * i)) & 15u; }

constexpr int PART = 72, HEADP = 64 * PART + 32;
__device__ __align__(128) float g_scratch[NH * HEADP];

#define DEVINL __device__ __forceinline__

DEVINL uint32_t smem_u32(const void* p) { return (uint32_t)__cvta_generic_to_shared(p); }
DEVINL void mbar_init(uint32_t b, uint32_t c) { asm volatile("mbarrier.init.shared::cta.b64 [%0], %1;" ::"r"(b), "r"(c) : "memory"); }
DEVINL void mbar_expect(uint32_t b, uint32_t tx) { asm volatile("mbarrier.arrive.expect_tx.shared::cta.b64 _, [%0], %1;" ::"r"(b), "r"(tx) : "memory"); }
DEVINL void mbar_arrive(uint32_t b) { asm volatile("mbarrier.arrive.shared::cta.b64 _, [%0];" ::"r"(b) : "memory"); }
DEVINL void mbar_wait(uint32_t b) {
    asm volatile(
        "{\n.reg .pred p;\n"
        "WAIT_%=:\n"
        "mbarrier.try_wait.parity.shared::cta.b64 p, [%0], 0;\n"
        "@!p bra WAIT_%=;\n"
        "}\n" ::"r"(b) : "memory");
}
DEVINL bool mbar_test(uint32_t b) {
    uint32_t ok;
    asm volatile("{.reg .pred p; mbarrier.test_wait.parity.shared::cta.b64 p, [%1], 0; selp.u32 %0,1,0,p;}" : "=r"(ok) : "r"(b) : "memory");
    return ok != 0;
}
DEVINL uint32_t clock32() { uint32_t t; asm volatile("mov.u32 %0, %globaltimer_lo;" : "=r"(t)); return t; }
DEVINL void tma_load3(uint32_t dst, const CUtensorMap* m, uint32_t bar, int c0, int c1, int c2, uint64_t pol) {
    asm volatile("cp.async.bulk.tensor.3d.shared::cluster.global.mbarrier::complete_tx::bytes.L2::cache_hint [%0], [%1, {%3,%4,%5}], [%2], %6;"
                 ::"r"(dst), "l"(m), "r"(bar), "r"(c0), "r"(c1), "r"(c2), "l"(pol) : "memory");
}
DEVINL void tma_store3(const CUtensorMap* m, uint32_t src, int c0, int c1, int c2) {
    asm volatile("cp.async.bulk.tensor.3d.global.shared::cta.bulk_group [%0, {%2,%3,%4}], [%1];"
                 ::"l"(m), "r"(src), "r"(c0), "r"(c1), "r"(c2) : "memory");
}
DEVINL void ldsm4(uint32_t (&r)[4], uint32_t a) {
    asm volatile("ldmatrix.sync.aligned.m8n8.x4.shared.b16 {%0,%1,%2,%3}, [%4];" : "=r"(r[0]), "=r"(r[1]), "=r"(r[2]), "=r"(r[3]) : "r"(a) : "memory");
}
DEVINL void ldsm4t(uint32_t (&r)[4], uint32_t a) {
    asm volatile("ldmatrix.sync.aligned.m8n8.x4.trans.shared.b16 {%0,%1,%2,%3}, [%4];" : "=r"(r[0]), "=r"(r[1]), "=r"(r[2]), "=r"(r[3]) : "r"(a) : "memory");
}
DEVINL void stsm4(uint32_t a, uint32_t r0, uint32_t r1, uint32_t r2, uint32_t r3) {
    asm volatile("stmatrix.sync.aligned.m8n8.x4.shared.b16 [%0], {%1,%2,%3,%4};" ::"r"(a), "r"(r0), "r"(r1), "r"(r2), "r"(r3) : "memory");
}
DEVINL uint32_t pack_bf16(float lo, float hi) {
    uint32_t r;
    asm("cvt.rn.bf16x2.f32 %0, %1, %2;" : "=r"(r) : "f"(hi), "f"(lo));
    return r;
}
DEVINL float ex2(float x) { float y; asm("ex2.approx.ftz.f32 %0, %1;" : "=f"(y) : "f"(x)); return y; }
DEVINL void mma16816(float (&d)[4], const uint32_t (&a)[4], uint32_t b0, uint32_t b1) {
    asm volatile("mma.sync.aligned.m16n8k16.row.col.f32.bf16.bf16.f32 {%0,%1,%2,%3}, {%4,%5,%6,%7}, {%8,%9}, {%0,%1,%2,%3};"
                 : "+f"(d[0]), "+f"(d[1]), "+f"(d[2]), "+f"(d[3]) : "r"(a[0]), "r"(a[1]), "r"(a[2]), "r"(a[3]), "r"(b0), "r"(b1));
}
DEVINL uint32_t movm_t(uint32_t a) { uint32_t d; asm volatile("movmatrix.sync.aligned.m8n8.trans.b16 %0, %1;" : "=r"(d) : "r"(a)); return d; }

DEVINL bool elect_one() {
    uint32_t p;
    asm volatile("{.reg .pred P; elect.sync _|P, 0xffffffff; selp.u32 %0, 1, 0, P;}" : "=r"(p));
    return p != 0;
}
DEVINL void wg_fence() { asm volatile("wgmma.fence.sync.aligned;" ::: "memory"); }
DEVINL void wg_commit() { asm volatile("wgmma.commit_group.sync.aligned;" ::: "memory"); }
template <int N> DEVINL void wg_wait() { asm volatile("wgmma.wait_group.sync.aligned %0;" ::"n"(N) : "memory"); }
template <int N> DEVINL void reg_fence(float (&d)[N]) {
#pragma unroll
    for (int i = 0; i < N; i++) asm volatile("" : "+f"(d[i])::"memory");
}
DEVINL uint64_t desc_at(uint32_t addr, uint32_t off) {
    uint64_t d;
    asm("mov.b64 %0, {%1, 0x40000040};" : "=l"(d) : "r"(((addr >> 4) | (1u << 16)) + off));
    return d;
}
#define ACC32 "{%0,%1,%2,%3,%4,%5,%6,%7,%8,%9,%10,%11,%12,%13,%14,%15,%16,%17,%18,%19,%20,%21,%22,%23,%24,%25,%26,%27,%28,%29,%30,%31}"
#define OPS32(c, d) c(d[0]), c(d[1]), c(d[2]), c(d[3]), c(d[4]), c(d[5]), c(d[6]), c(d[7]), c(d[8]), c(d[9]), c(d[10]), c(d[11]), \
    c(d[12]), c(d[13]), c(d[14]), c(d[15]), c(d[16]), c(d[17]), c(d[18]), c(d[19]), c(d[20]), c(d[21]), c(d[22]), c(d[23]),     \
    c(d[24]), c(d[25]), c(d[26]), c(d[27]), c(d[28]), c(d[29]), c(d[30]), c(d[31])
template <int TRANS_B>
DEVINL void wgmma_n64(float (&d)[32], uint32_t a0, uint32_t a1, uint32_t a2, uint32_t a3, uint64_t desc, bool acc) {
    if (acc)
        asm volatile("wgmma.mma_async.sync.aligned.m64n64k16.f32.bf16.bf16 " ACC32 ", {%32,%33,%34,%35}, %36, 1, 1, 1, %37;"
                     : OPS32("+f", d) : "r"(a0), "r"(a1), "r"(a2), "r"(a3), "l"(desc), "n"(TRANS_B));
    else
        asm volatile("wgmma.mma_async.sync.aligned.m64n64k16.f32.bf16.bf16 " ACC32 ", {%32,%33,%34,%35}, %36, 0, 1, 1, %37;"
                     : OPS32("=f", d) : "r"(a0), "r"(a1), "r"(a2), "r"(a3), "l"(desc), "n"(TRANS_B));
}
DEVINL void wgmma_n8(float (&d)[4], uint32_t a0, uint32_t a1, uint32_t a2, uint32_t a3, uint64_t desc, bool acc) {
    if (acc)
        asm volatile("wgmma.mma_async.sync.aligned.m64n8k16.f32.bf16.bf16 {%0,%1,%2,%3}, {%4,%5,%6,%7}, %8, 1, 1, 1, 0;"
                     : "+f"(d[0]), "+f"(d[1]), "+f"(d[2]), "+f"(d[3]) : "r"(a0), "r"(a1), "r"(a2), "r"(a3), "l"(desc));
    else
        asm volatile("wgmma.mma_async.sync.aligned.m64n8k16.f32.bf16.bf16 {%0,%1,%2,%3}, {%4,%5,%6,%7}, %8, 0, 1, 1, 0;"
                     : "=f"(d[0]), "=f"(d[1]), "=f"(d[2]), "=f"(d[3]) : "r"(a0), "r"(a1), "r"(a2), "r"(a3), "l"(desc));
}
DEVINL void sts4(uint32_t a, uint32_t x, uint32_t y, uint32_t z, uint32_t w) {
    asm volatile("st.shared.v4.u32 [%0], {%1,%2,%3,%4};" ::"r"(a), "r"(x), "r"(y), "r"(z), "r"(w) : "memory");
}
DEVINL void sts2f(uint32_t a, float x, float y) { asm volatile("st.shared.v2.f32 [%0], {%1,%2};" ::"r"(a), "f"(x), "f"(y) : "memory"); }
DEVINL float2 lds2f(uint32_t a) { float2 r; asm volatile("ld.shared.v2.f32 {%0,%1}, [%2];" : "=f"(r.x), "=f"(r.y) : "r"(a) : "memory"); return r; }
DEVINL uint32_t tagged(float x, uint32_t tag) { return (__float_as_uint(x) & ~1u) | tag; }
DEVINL void st_vol4(float* p, uint32_t a, uint32_t b, uint32_t c, uint32_t d) {
    asm volatile("st.relaxed.gpu.global.v4.u32 [%0], {%1,%2,%3,%4};" ::"l"(p), "r"(a), "r"(b), "r"(c), "r"(d) : "memory");
}
DEVINL uint32_t ld_rlx(const float* p) {
    uint32_t r;
    asm volatile("ld.relaxed.gpu.global.u32 %0, [%1];" : "=r"(r) : "l"(p) : "memory");
    return r;
}

constexpr float SCALE_LOG2 = 0.0625f * 1.4426950408889634f;

__device__ __noinline__ void generic_path(const __nv_bfloat16* __restrict__ q, const __nv_bfloat16* __restrict__ k,
                                          const __nv_bfloat16* __restrict__ v, __nv_bfloat16* __restrict__ out,
                                          int window, int ng) {
    const int lane = threadIdx.x & 31, warp = threadIdx.x >> 5;
    const int h = blockIdx.x >> 3, c = blockIdx.x & 7;
    for (int r = warp; r < 256; r += 12) {
        const int row = c * 256 + r;
        float qv[8], acc[8];
        {
            uint4 u = *(const uint4*)(q + ((size_t)h * SEQ + row) * HD + lane * 8);
            const __nv_bfloat16* p = (const __nv_bfloat16*)&u;
            for (int i = 0; i < 8; i++) { qv[i] = __bfloat162float(p[i]); acc[i] = 0.f; }
        }
        float m = -INFINITY, l = 0.f;
        for (int j = 0; j < SEQ; j++) {
            const long long dist = (long long)row - j;
            const bool ok = (dist <= window && dist >= -(long long)window) || row < ng || j < ng;
            float s = -1e9f;
            if (ok) {
                uint4 u = *(const uint4*)(k + ((size_t)h * SEQ + j) * HD + lane * 8);
                const __nv_bfloat16* p = (const __nv_bfloat16*)&u;
                s = 0.f;
                for (int i = 0; i < 8; i++) s += qv[i] * __bfloat162float(p[i]);
                for (int o = 16; o > 0; o >>= 1) s += __shfl_xor_sync(0xffffffffu, s, o);
                s *= 0.0625f;
            }
            const float mn = fmaxf(m, s);
            const float a = __expf(m - mn), p = __expf(s - mn);
            m = mn;
            l = l * a + p;
            if (p != 0.f || a != 1.f) {
                uint4 u = *(const uint4*)(v + ((size_t)h * SEQ + j) * HD + lane * 8);
                const __nv_bfloat16* pv = (const __nv_bfloat16*)&u;
                for (int i = 0; i < 8; i++) acc[i] = acc[i] * a + p * __bfloat162float(pv[i]);
            }
        }
        const float inv = 1.f / l;
        uint4 o;
        o.x = pack_bf16(acc[0] * inv, acc[1] * inv); o.y = pack_bf16(acc[2] * inv, acc[3] * inv);
        o.z = pack_bf16(acc[4] * inv, acc[5] * inv); o.w = pack_bf16(acc[6] * inv, acc[7] * inv);
        *(uint4*)(out + ((size_t)h * SEQ + row) * HD + lane * 8) = o;
    }
}

DEVINL void consumer(const int wg, const int warp, const int lane, const int q_first) {
    const int g = lane >> 2, cq = lane & 3;
    const int lrow = warp * 16 + (lane & 7) + ((lane >> 3) & 1) * 8;
    const int lcol = lane >> 4;
    const int dd = warp * 16 + g - 2 * cq;
    const bool has_diag = (unsigned)(g - 2 * cq) < 2u;
    mbar_wait(bars + 8 * B_GR);
#pragma unroll 1
    for (int t = wg; t < 4; t += 2) {
        const int q0 = q_first + 64 * t;
        const uint32_t fb = bars + 8 * (B_FULL + 12 * t);
        const uint32_t slots = (uint32_t)(TAB_SLOT >> (12 * t));
        const uint32_t q_addr = base + ((slots >> 8) & 7u) * 32768u + lrow * 128;
        const uint32_t hi_shift = (SPLIT3 && t == 3) ? Q3_HI_SHIFT : 0u;
        uint32_t pL[16], pU[16], pg[2];
        float lsum[2];
        {
            const uint32_t rb = bars + 8 * (B_REL + 3 * t);
            const uint64_t dK1 = desc_at(base, (slots & 7u) * 2048u), dKG = desc_at(base + SM_KG, 0);
            const uint64_t dK2l = desc_at(base, (SPLIT3 && t == 3) ? SM_X / 16 : ((slots >> 12) & 7u) * 2048u);
            const uint64_t dK2h = desc_at(base, ((slots >> ((SPLIT3 && t == 3) ? 8 : 12)) & 7u) * 2048u);
            float sL[32], sU[32], sg[4];
            uint32_t qf[8][4];
#pragma unroll
            for (int ch = 0; ch < 4; ch++) {
                mbar_wait(fb + 8 * ch);
                mbar_wait(fb + 8 * (12 + ch));
                mbar_wait(fb + 8 * (8 + ch));
                if (ch >= 2) wg_wait<1>();
#pragma unroll
                for (int ks = 0; ks < 4; ks++)
                    ldsm4(qf[(ch & 1) * 4 + ks], q_addr + (ch >= 2 ? hi_shift : 0u) + ch * 8192 + (((ks * 2 + lcol) ^ (lrow & 7)) << 4));
                if (ch == 3) {
                    __syncwarp();
                    if (elect_one()) mbar_arrive(rb + 16);
                    if (warp == 0) TLOG(t * 8 + 0);
                }
                wg_fence();
#pragma unroll
                for (int ks = 0; ks < 4; ks++) {
                    const int i = (ch & 1) * 4 + ks, acc = ch + ks != 0;
                    wgmma_n8(sg, qf[i][0], qf[i][1], qf[i][2], qf[i][3], dKG + (ch * 64 + ks * 2), acc);
                    wgmma_n64<0>(sL, qf[i][0], qf[i][1], qf[i][2], qf[i][3], dK1 + (ch * 512 + ks * 2), acc);
                    wgmma_n64<0>(sU, qf[i][0], qf[i][1], qf[i][2], qf[i][3], (ch < 2 ? dK2l : dK2h) + (ch * 512 + ks * 2), acc);
                }
                wg_commit();
            }
            wg_wait<0>();
            if (elect_one()) { mbar_arrive(rb); mbar_arrive(rb + 24); }
            reg_fence(sL); reg_fence(sU); reg_fence(sg);
            if (warp == 0) TLOG(t * 8 + 2);
            if (q0 == 0 || q0 == SEQ - 64) {
                asm volatile("");
                if (q0 == 0) {
#pragma unroll
                    for (int i = 0; i < 16; i++) sL[i] = -INFINITY;
                    if (cq == 0) { sL[16] = sL[17] = sL[18] = sL[19] = -INFINITY; }
                } else {
#pragma unroll
                    for (int i = 16; i < 32; i++) sU[i] = -INFINITY;
                }
            }
            float x[2][19], m[2];
#pragma unroll
            for (int r = 0; r < 2; r++) {
#pragma unroll
                for (int i = 0; i < 8; i++)
#pragma unroll
                    for (int e = 0; e < 2; e++)
                        x[r][2 * i + e] = (8 * (i - r) + e >= dd) ? sL[4 * i + 2 * r + e] : sU[4 * i + 2 * r + e];
                float z[4];
#pragma unroll
                for (int w = 0; w < 4; w++) z[w] = (g & 1) ? sU[8 * w + 6 * r + 1] : sU[8 * w + 6 * r];
                const float zz = warp < 2 ? (warp == 0 ? z[0] : z[1]) : (warp == 2 ? z[2] : z[3]);
                x[r][16] = has_diag ? zz : -INFINITY;
                x[r][17] = cq == 0 ? sg[2 * r] : -INFINITY;
                x[r][18] = cq == 0 ? sg[2 * r + 1] : -INFINITY;
            }
#pragma unroll
            for (int r = 0; r < 2; r++) {
                float u[4];
#pragma unroll
                for (int i = 0; i < 4; i++) u[i] = fmaxf(fmaxf(x[r][4 * i], x[r][4 * i + 1]), fmaxf(x[r][4 * i + 2], x[r][4 * i + 3]));
                m[r] = fmaxf(fmaxf(fmaxf(u[0], u[1]), fmaxf(u[2], u[3])), fmaxf(x[r][16], fmaxf(x[r][17], x[r][18])));
                m[r] = fmaxf(m[r], __shfl_xor_sync(0xffffffffu, m[r], 1));
                m[r] = fmaxf(m[r], __shfl_xor_sync(0xffffffffu, m[r], 2));
            }
#pragma unroll
            for (int r = 0; r < 2; r++) {
                const float mc = -m[r] * SCALE_LOG2;
#pragma unroll
                for (int i = 0; i < 19; i++) x[r][i] = ex2(fmaf(x[r][i], SCALE_LOG2, mc));
                float u[4];
#pragma unroll
                for (int i = 0; i < 4; i++) u[i] = (x[r][4 * i] + x[r][4 * i + 1]) + (x[r][4 * i + 2] + x[r][4 * i + 3]);
                lsum[r] = ((u[0] + u[1]) + (u[2] + u[3])) + (x[r][16] + (x[r][17] + x[r][18]));
                const uint32_t pd = pack_bf16(x[r][16], 0.f) << (16 * (g & 1));
                pg[r] = pack_bf16(x[r][17], x[r][18]);
#pragma unroll
                for (int i = 0; i < 8; i++) {
                    uint32_t mk;
                    asm("shl.b32 %0, 0xffffffff, %1;" : "=r"(mk) : "r"(max(16 * dd - 128 * (i - r), 0)));
                    const uint32_t pp = pack_bf16(x[r][2 * i], x[r][2 * i + 1]);
                    pL[2 * i + r] = pp & mk;
                    pU[2 * i + r] = pp & ~mk;
                    if ((i & 1) == r) pU[2 * i + r] |= (warp == (i >> 1)) ? pd : 0u;
                }
            }
            if (warp == 0) TLOG(t * 8 + 3);
        }
        const int srow = (lrow + (q0 == 0 ? 64 - FAST_G : 0)) & 63;
        const uint32_t st_addr = t == 3 ? q_addr : base + ((slots >> 4) & 7u) * 32768u + srow * 128;
        const uint64_t dV1 = desc_at(base, ((slots >> 4) & 7u) * 2048u), dV2 = desc_at(base, ((slots >> 16) & 7u) * 2048u);
        const uint64_t dVG = desc_at(base + SM_VG, 0);
        float oa[32], ob[32], inv0, inv1;
        uint32_t y[16];
        auto mma = [&](float (&o)[32], int ch) {
            mbar_wait(fb + 8 * (4 + ch));
            mbar_wait(fb + 8 * (16 + ch));
            wg_fence();
            wgmma_n64<1>(o, pg[0], pg[1], 0u, 0u, dVG + ch * 128, false);
#pragma unroll
            for (int kk = 0; kk < 4; kk++)
                wgmma_n64<1>(o, pL[4 * kk], pL[4 * kk + 1], pL[4 * kk + 2], pL[4 * kk + 3], dV1 + (ch * 512 + kk * 128), true);
#pragma unroll
            for (int kk = 0; kk < 4; kk++)
                wgmma_n64<1>(o, pU[4 * kk], pU[4 * kk + 1], pU[4 * kk + 2], pU[4 * kk + 3], dV2 + (ch * 512 + kk * 128), true);
            wg_commit();
        };
        auto pack = [&](float (&o)[32]) {
            reg_fence(o);
#pragma unroll
            for (int i = 0; i < 8; i++) {
                y[2 * i] = pack_bf16(o[4 * i] * inv0, o[4 * i + 1] * inv0);
                y[2 * i + 1] = pack_bf16(o[4 * i + 2] * inv1, o[4 * i + 3] * inv1);
                asm volatile("" : "+r"(y[2 * i]), "+r"(y[2 * i + 1]));
            }
        };
        auto stage = [&](int ch) {
            if (t != 3) asm volatile("bar.sync %0, 128;" ::"r"(2 + wg) : "memory");
#pragma unroll
            for (int i = 0; i < 8; i += 2)
                stsm4(st_addr + (ch >= 2 ? hi_shift : 0u) + ch * 8192 + (((i + lcol) ^ (srow & 7)) << 4), y[2 * i], y[2 * i + 1], y[2 * i + 2], y[2 * i + 3]);
            asm volatile("fence.proxy.async.shared::cta;" ::: "memory");
            __syncwarp();
            if (elect_one()) mbar_arrive(bars + 8 * (B_SF + t * 4 + ch));
            if (warp == 0) TLOG(t * 8 + 4 + ch);
        };
        mma(oa, 0);
        lsum[0] += __shfl_xor_sync(0xffffffffu, lsum[0], 1);
        lsum[1] += __shfl_xor_sync(0xffffffffu, lsum[1], 1);
        lsum[0] += __shfl_xor_sync(0xffffffffu, lsum[0], 2);
        lsum[1] += __shfl_xor_sync(0xffffffffu, lsum[1], 2);
        asm("rcp.approx.ftz.f32 %0, %1;" : "=f"(inv0) : "f"(lsum[0]));
        asm("rcp.approx.ftz.f32 %0, %1;" : "=f"(inv1) : "f"(lsum[1]));
        mma(ob, 1);
        if (t != 3) mbar_wait(bars + 8 * (B_GV + t));
        wg_wait<1>(); pack(oa); stage(0);
        mma(oa, 2); wg_wait<1>(); pack(ob); stage(1);
        mma(ob, 3); wg_wait<1>(); pack(oa); stage(2);
        wg_wait<0>();
        if (elect_one()) mbar_arrive(bars + 8 * (B_GV + t + 1));
        pack(ob); stage(3);
    }
}

__global__ void __launch_bounds__(384, 1)
attn_kernel(const __grid_constant__ Maps maps, const __nv_bfloat16* __restrict__ q, const __nv_bfloat16* __restrict__ k,
            const __nv_bfloat16* __restrict__ v, const int* __restrict__ p_window, const int* __restrict__ p_ng,
            __nv_bfloat16* __restrict__ out, float* __restrict__ scratch) {
    extern __shared__ __align__(1024) uint8_t smem_raw[];
    const uint32_t t_start = clock32();
    if (smem_u32(smem_raw) != base) {
        generic_path(q, k, v, out, __ldg(p_window), __ldg(p_ng));
        return;
    }
    const int lane = threadIdx.x & 31;
    const int h = blockIdx.x >> 3, c = blockIdx.x & 7;
    const int q_first = c * 256;

    uint64_t pol_first, pol_norm;
    asm volatile("createpolicy.fractional.L2::evict_first.b64 %0, 1.0;" : "=l"(pol_first));
    asm volatile("createpolicy.fractional.L2::evict_normal.b64 %0, 1.0;" : "=l"(pol_norm));

    static_assert(nib(TAB_ORD, 0) == K0 && nib(TAB_PSLOT, 0) == 0, "prologue assumes K0 first");
    if (threadIdx.x >= 320 && threadIdx.x < 352) {
        if (elect_one()) {
#pragma unroll
            for (int ch = 0; ch < 4; ch++) {
                mbar_init(bars + 8 * ch, 1);
                mbar_expect(bars + 8 * ch, 8192);
                tma_load3(base + ch * 8192, &maps.k32, bars + 8 * ch, ch * 64, (q_first - 32) & (SEQ - 1), h, pol_norm);
                tma_load3(base + ch * 8192 + 4096, &maps.k32, bars + 8 * ch, ch * 64, q_first, h, pol_norm);
                if (ch == 0) TLOG(46);
            }
            TLOG(47);
        }
        __syncwarp();
    }
    const int warp = __shfl_sync(0xffffffffu, threadIdx.x >> 5, 0);
    if (warp == 0) TLOG(127);
    int window, ng;
    asm volatile("ld.global.nc.u32 %0, [%1];" : "=r"(window) : "l"(p_window));
    asm volatile("ld.global.nc.u32 %0, [%1];" : "=r"(ng) : "l"(p_ng));
    uint4 kx, vx;
    uint32_t qb[16][2], epoch;
    float* const part = scratch + h * HEADP;
    if (warp == 8 || warp == 9) {
        const int g = lane >> 2, cq = lane & 3;
        kx = __ldg((const uint4*)(k + ((size_t)h * SEQ + (warp - 8)) * HD) + lane);
        vx = __ldg((const uint4*)(v + ((size_t)h * SEQ + (warp - 8)) * HD) + lane);
        epoch = ld_rlx(part + 64 * PART);
        const uint32_t* qp = (const uint32_t*)(q + ((size_t)h * SEQ + (g & 1)) * HD + 2 * cq);
#pragma unroll
        for (int ks = 0; ks < 16; ks++) { qb[ks][0] = __ldg(qp + ks * 8); qb[ks][1] = __ldg(qp + ks * 8 + 4); }
    } else if (warp == 11) {
        if (elect_one()) {
            asm volatile("prefetch.tensormap [%0];" ::"l"(&maps.k) : "memory");
            asm volatile("prefetch.tensormap [%0];" ::"l"(&maps.q) : "memory");
            asm volatile("prefetch.tensormap [%0];" ::"l"(&maps.v32) : "memory");
            asm volatile("prefetch.tensormap [%0];" ::"l"(&maps.v) : "memory");
            asm volatile("prefetch.tensormap [%0];" ::"l"(&maps.o) : "memory");
            asm volatile("prefetch.tensormap [%0];" ::"l"(&maps.o62) : "memory");
#pragma unroll
            for (int i = 0; i < 13; i++) mbar_init(bars + 8 * (B_REL + i), i % 3 == 2 ? 4 : i % 3 == 1 ? 1 : i == 0 ? 6 : 10);
#pragma unroll
            for (int i = 0; i < 5; i++) mbar_init(bars + 8 * (B_GV + i), i == 0 ? 2 : 6);
            mbar_init(bars + 8 * B_GR, 2);
#pragma unroll
            for (int i = 4; i < 8; i++) mbar_init(bars + 8 * i, 1);
        }
    } else if (warp < 8) {
        if (elect_one()) {
#pragma unroll
            for (int i = 0; i < 6; i++) mbar_init(bars + 8 * (B_FULL + 8 + warp * 6 + i), 1);
#pragma unroll
            for (int i = 0; i < 2; i++) mbar_init(bars + 8 * (B_SF + warp * 2 + i), 4);
        }
    }
    __syncthreads();

    if (warp == 10) {
        static_assert(WIN >= 1 && WIN <= 12 && WHI >= WIN && WHI <= 12, "window history holds three blocks");
        int dl = TOFF + 4 * TAU;
        uint32_t fbh[4] = {0u, bars, bars, bars};
#pragma unroll 1
        for (int pos = 1; pos < (HITSEP ? 12 : 14); pos++) {
            const uint32_t blk = nib(TAB_ORD, pos);
            const uint32_t idx = (blk * 11) >> 5, type = blk - 3 * idx;
            uint32_t dst = base + nib(TAB_PSLOT, pos) * 32768u;
            const uint32_t fb = bars + 32 * blk;
            const int row = q_first + idx * 64 - (type == 2 ? 0 : 32);
            int tau = pos >= PFAST ? TAUF : blk < K4 ? TAU : 0;
            if (STAGE && pos == 11) { tau = TAU / 2; if (blockIdx.x & 2) dl += 2 * TAU; }
            const CUtensorMap* const map = &maps.k + (blk == V0 ? 3 : type);
            const uint64_t pol = blk == V0 ? pol_norm : pol_first;
            fbh[0] = fb;
            if (pos >= 6) {
                if (pos == 6) {
                    int bad;
                    asm volatile("{.reg .b32 a, b; xor.b32 a, %1, %3; xor.b32 b, %2, %4; or.b32 %0, a, b;}"
                                 : "=r"(bad) : "r"(window), "r"(ng), "n"(FAST_W), "n"(FAST_G));
                    if (__shfl_sync(0xffffffffu, bad, 0) != 0) break;
                }
                mbar_wait(bars + 8 * (B_REL + nib(TAB_PREV, pos)));
            }
#pragma unroll
            for (int ch = 0; ch < 4; ch++) {
                if (pos * 4 + ch >= WHI) mbar_wait(fbh[(WHI - ch + 3) >> 2] + 8 * ((ch - WHI) & 3));
                while (!mbar_test(fbh[(WIN - ch + 3) >> 2] + 8 * ((ch - WIN) & 3)) && (int)(clock32() - t_start) < dl) {}
                if (SPLIT3 && ch == 2 && blk == Q3) { mbar_wait(bars + 8 * (B_REL + Q2)); dst += Q3_HI_SHIFT; }
                if (elect_one()) {
                    mbar_expect(fb + 8 * ch, 8192);
                    tma_load3(dst + ch * 8192, map, fb + 8 * ch, ch * 64, row & (SEQ - 1), h, pol);
                    if (blk == V0) tma_load3(dst + ch * 8192 + 4096, map, fb + 8 * ch, ch * 64, row + 32, h, pol);
                }
                dl += tau;
                if (ch == 0) TLOG(48 + pos);
            }
            fbh[3] = fbh[2]; fbh[2] = fbh[1]; fbh[1] = fb;
        }
    }

    if (window != FAST_W || ng != FAST_G) {
#pragma unroll 1
        for (int p = 0; p < 24; p++) mbar_wait(bars + 32 * nib(TAB_ORD, p >> 2) + 8 * (p & 3));
        generic_path(q, k, v, out, window, ng);
        return;
    }

    if (warp < 8) {
        consumer(warp >> 2, warp & 3, lane, q_first);
    } else if (warp < 10) {
        const int gw = warp - 8, tid = threadIdx.x - 256;
        const int g = lane >> 2, cq = lane & 3;
        const uint32_t tag = (epoch + 1u) & 1u;
        {
#pragma unroll 1
            for (int i = 0; i < 12; i++)
                if (tid >= 16 || (i >= 4 && (i & 1)))
                    asm volatile("st.shared.v4.u32 [%0], {%1,%1,%1,%1};" ::"r"(base + SM_KG + i * 1024 + tid * 16), "r"(0u) : "memory");
            const uint32_t sw = gw * 128 + (((lane & 7) ^ gw) << 4);
            asm volatile("st.shared.v4.u32 [%0], {%1,%2,%3,%4};" ::"r"(base + SM_KG + (lane >> 3) * 1024 + sw), "r"(kx.x), "r"(kx.y), "r"(kx.z), "r"(kx.w) : "memory");
            asm volatile("st.shared.v4.u32 [%0], {%1,%2,%3,%4};" ::"r"(base + SM_VG + (lane >> 3) * 2048 + sw), "r"(vx.x), "r"(vx.y), "r"(vx.z), "r"(vx.w) : "memory");
            asm volatile("fence.proxy.async.shared::cta;" ::: "memory");
            __syncwarp();
            if (elect_one()) mbar_arrive(bars + 8 * B_GR);
        }
        if (warp == 8) TLOG(32);
        float oacc[16][4];
#pragma unroll
        for (int i = 0; i < 16; i++) { oacc[i][0] = oacc[i][1] = oacc[i][2] = oacc[i][3] = 0.f; }
        float m0 = -1e30f, m1 = -1e30f, l0 = 0.f, l1 = 0.f;
        const int krow = gw * 32 + (lane & 7) + ((lane >> 3) & 1) * 8;
        const int vrow = gw * 32 + (lane & 7) + (lane >> 4) * 8;
#pragma unroll 1
        for (int j = 0; j < 4; j++) {
            const uint32_t fb = bars + 8 * (B_FULL + 12 * j);
            const uint32_t slots = (uint32_t)(TAB_SLOT >> (12 * j));
            const uint32_t kb = base + (slots & 7u) * 32768u + krow * 128;
            const uint32_t vb = base + ((slots >> 4) & 7u) * 32768u + vrow * 128;
            float sa[4] = {0.f, 0.f, 0.f, 0.f}, sb[4] = {0.f, 0.f, 0.f, 0.f};
#pragma unroll
            for (int ch = 0; ch < 4; ch++) {
                mbar_wait(fb + 8 * ch);
#pragma unroll
                for (int ks = 0; ks < 4; ks++) {
                    uint32_t a[4], b[4];
                    const uint32_t off = ch * 8192 + (((ks * 2 + (lane >> 4)) ^ (lane & 7)) << 4);
                    ldsm4(a, kb + off);
                    ldsm4(b, kb + off + 2048);
                    mma16816(sa, a, qb[ch * 4 + ks][0], qb[ch * 4 + ks][1]);
                    mma16816(sb, b, qb[ch * 4 + ks][0], qb[ch * 4 + ks][1]);
                }
            }
            __syncwarp();
            if (elect_one()) mbar_arrive(bars + 8 * (B_REL + 3 * j));
            if (warp == 8) TLOG(33 + 2 * j);
            uint32_t pb[4];
            {
                float t0 = fmaxf(fmaxf(sa[0], sa[2]), fmaxf(sb[0], sb[2])), t1 = fmaxf(fmaxf(sa[1], sa[3]), fmaxf(sb[1], sb[3]));
#pragma unroll
                for (int o = 4; o < 32; o <<= 1) {
                    t0 = fmaxf(t0, __shfl_xor_sync(0xffffffffu, t0, o));
                    t1 = fmaxf(t1, __shfl_xor_sync(0xffffffffu, t1, o));
                }
                const float n0 = fmaxf(m0, t0), n1 = fmaxf(m1, t1);
                const float a0 = ex2((m0 - n0) * SCALE_LOG2), a1 = ex2((m1 - n1) * SCALE_LOG2);
                m0 = n0; m1 = n1;
                l0 *= a0; l1 *= a1;
#pragma unroll
                for (int i = 0; i < 4; i++) {
                    const float e0 = ex2(((i < 2 ? sa[2 * i] : sb[2 * i - 4]) - n0) * SCALE_LOG2);
                    const float e1 = ex2(((i < 2 ? sa[2 * i + 1] : sb[2 * i - 3]) - n1) * SCALE_LOG2);
                    l0 += e0; l1 += e1;
                    pb[i] = movm_t(pack_bf16(e0, e1));
                }
#pragma unroll
                for (int i = 0; i < 16; i++) { oacc[i][0] *= a0; oacc[i][1] *= a1; oacc[i][2] *= a0; oacc[i][3] *= a1; }
            }
#pragma unroll
            for (int ch = 0; ch < 4; ch++) {
                mbar_wait(fb + 8 * (4 + ch));
#pragma unroll
                for (int mt = 0; mt < 4; mt++) {
                    uint32_t a[4], b[4];
                    const uint32_t off = ch * 8192 + (((mt * 2 + ((lane >> 3) & 1)) ^ (lane & 7)) << 4);
                    ldsm4t(a, vb + off);
                    ldsm4t(b, vb + off + 2048);
                    mma16816(oacc[ch * 4 + mt], a, pb[0], pb[1]);
                    mma16816(oacc[ch * 4 + mt], b, pb[2], pb[3]);
                }
            }
            __syncwarp();
            if (elect_one()) mbar_arrive(bars + 8 * (B_GV + j));
            if (warp == 8) TLOG(34 + 2 * j);
        }
#pragma unroll
        for (int o = 4; o < 32; o <<= 1) {
            l0 += __shfl_xor_sync(0xffffffffu, l0, o);
            l1 += __shfl_xor_sync(0xffffffffu, l1, o);
        }
        float* gr = (float*)(smem_raw + SM_GR);
        float* my = gr + gw * 544;
#pragma unroll
        for (int i = 0; i < 4; i++) {
            float y[4];
#pragma unroll
            for (int e = 0; e < 4; e++)
                y[e] = cq < 2 ? (cq == 0 ? oacc[i][e] : oacc[4 + i][e]) : (cq == 2 ? oacc[8 + i][e] : oacc[12 + i][e]);
            *(float2*)(my + 2 * ((cq * 4 + i) * 16 + g)) = make_float2(y[0], y[1]);
            *(float2*)(my + 2 * ((cq * 4 + i) * 16 + g + 8)) = make_float2(y[2], y[3]);
        }
        if (lane == 0) *(float4*)(my + 512) = make_float4(m0, m1, l0, l1);
        asm volatile("bar.sync 1, 64;" ::: "memory");
        {
            const float4 ma = *(const float4*)(gr + 512), mb = *(const float4*)(gr + 544 + 512);
            const float mm0 = fmaxf(ma.x, mb.x), mm1 = fmaxf(ma.y, mb.y);
            const float wa0 = ex2((ma.x - mm0) * SCALE_LOG2), wb0 = ex2((mb.x - mm0) * SCALE_LOG2);
            const float wa1 = ex2((ma.y - mm1) * SCALE_LOG2), wb1 = ex2((mb.y - mm1) * SCALE_LOG2);
            const float4 a0 = *(const float4*)(gr + tid * 4), a1 = *(const float4*)(gr + tid * 4 + 256);
            const float4 b0 = *(const float4*)(gr + 544 + tid * 4), b1 = *(const float4*)(gr + 544 + tid * 4 + 256);
            float* const dst = part + ((tid >> 4) * 8 + c) * PART + (tid & 15) * 4;
            st_vol4(dst, tagged(a0.x * wa0 + b0.x * wb0, tag), tagged(a0.y * wa1 + b0.y * wb1, tag),
                    tagged(a0.z * wa0 + b0.z * wb0, tag), tagged(a0.w * wa1 + b0.w * wb1, tag));
            st_vol4(dst + 32 * PART, tagged(a1.x * wa0 + b1.x * wb0, tag), tagged(a1.y * wa1 + b1.y * wb1, tag),
                    tagged(a1.z * wa0 + b1.z * wb0, tag), tagged(a1.w * wa1 + b1.w * wb1, tag));
            if (tid < 16)
                st_vol4(part + ((tid >> 1) * 8 + c) * PART + 64 + (tid & 1) * 4, tagged(mm0, tag), tagged(mm1, tag),
                        tagged(ma.z * wa0 + mb.z * wb0, tag), tagged(ma.w * wa1 + mb.w * wb1, tag));
        }
        if (warp == 8) TLOG(43);
        {
            const float* const src = part + c * 8 * PART;
            int spins = 0;
            uint32_t x[8], ml;
            if (POLLWAIT >= 0) mbar_wait(bars + 8 * POLLWAIT);
            while (true) {
                if (POLLNS && (POLLWAIT < 0 || spins)) __nanosleep(POLLNS);
                ml = ld_rlx(src + (lane & 7) * PART + 64 + (lane >> 3));
                uint32_t bad = ml ^ tag;
#pragma unroll
                for (int i = 0; i < 8; i++) { x[i] = ld_rlx(src + i * PART + tid); bad |= x[i] ^ tag; }
                if (!__any_sync(0xffffffffu, (bad & 1u) != 0u)) break;
                if (++spins > (1 << 22)) __trap();
            }
            if (warp == 8) TLOG(44);
            const float mi = __uint_as_float(ml);
            float M = mi;
#pragma unroll
            for (int o = 1; o < 8; o <<= 1) M = fmaxf(M, __shfl_xor_sync(0xffffffffu, M, o));
            const float w = ex2((mi - M) * SCALE_LOG2);
            float L = __shfl_xor_sync(0xffffffffu, mi, 16) * w, r = 0.f;
#pragma unroll
            for (int o = 1; o < 8; o <<= 1) L += __shfl_xor_sync(0xffffffffu, L, o);
#pragma unroll
            for (int i = 0; i < 8; i++) r = fmaf(__uint_as_float(x[i]), __shfl_sync(0xffffffffu, w, (lane & 1) * 8 + i), r);
            L = __shfl_sync(0xffffffffu, L, (lane & 1) * 8);
            out[((size_t)h * SEQ + (tid & 1)) * HD + c * 32 + (tid >> 1)] = __float2bfloat16(__fdividef(r, L));
            if (c == 0 && tid == 0) *(volatile uint32_t*)(part + 64 * PART) = epoch + 1u;
        }
        if (warp == 8) TLOG(45);
    } else if (warp == 11) {
        if (elect_one()) {
#pragma unroll 1
            for (int t = 0; t < 4; t++) {
                const int q0 = q_first + t * 64;
                const CUtensorMap* m = q0 == 0 ? &maps.o62 : &maps.o;
                const int row = q0 == 0 ? FAST_G : q0;
                const uint32_t src = base + nib(TAB_SLOT, t == 3 ? Q3 : 3 * t + 1) * 32768u;
                if (HITSEP && (t == 2 || (SPLIT3 && t == 0))) {
                    static_assert(!HITSEP || (nib(TAB_ORD, 12) == K4 && nib(TAB_ORD, 13) == V4), "");
                    static_assert(!SPLIT3 || (nib(TAB_PREV, 11) == V1 && nib(TAB_PREV, 12) == Q2), "");
#pragma unroll 1
                    for (int i = SPLIT3 ? t : 0; i < (t == 0 ? 2 : 8); i++) {
                        if (i == 4 || (!SPLIT3 && i == 0)) mbar_wait(bars + 8 * (B_REL + nib(TAB_PREV, 12 + (i >> 2))));
                        const uint32_t dst = SPLIT3 && i < 4 ? (i < 2 ? SM_X : slot_of(Q3) * 32768u) : nib(TAB_PSLOT, 12 + (i >> 2)) * 32768u;
                        mbar_expect(bars + 8 * (4 * K4 + i), 8192);
                        tma_load3(base + dst + (i & 3) * 8192, &maps.k + (i >> 2), bars + 8 * (4 * K4 + i), (i & 3) * 64, q_first + 224, h, pol_first);
                        if ((i & 3) == 2) TLOG(60 + (i >> 2));
                    }
                }
                if (DEFER >= 0 && t == 2) mbar_wait(bars + 8 * (B_FULL + 4 * Q3 + DEFER));
#pragma unroll 1
                for (int ch = 0; ch < 4; ch++) {
                    mbar_wait(bars + 8 * (B_SF + t * 4 + ch));
                    tma_store3(m, src + (SPLIT3 && t == 3 && ch >= 2 ? Q3_HI_SHIFT : 0u) + ch * 8192, ch * 64, row, h);
                    asm volatile("cp.async.bulk.commit_group;" ::: "memory");
                    TLOG(64 + t * 4 + ch);
                }
                if (t != 2) {
                    asm volatile("cp.async.bulk.wait_group.read 0;" ::: "memory");
                    mbar_arrive(bars + 8 * (B_REL + 3 * t + 1));
                }
                TLOG(80 + t);
            }
        }
    }
}

typedef CUresult (*EncodeFn)(CUtensorMap*, CUtensorMapDataType, cuuint32_t, void*, const cuuint64_t*, const cuuint64_t*,
                             const cuuint32_t*, const cuuint32_t*, CUtensorMapInterleave, CUtensorMapSwizzle,
                             CUtensorMapL2promotion, CUtensorMapFloatOOBfill);

void make_map(EncodeFn f, CUtensorMap* m, void* p, unsigned rows) {
    cuuint64_t dims[3] = {HD, SEQ, NH};
    cuuint64_t strides[2] = {HD * 2, (cuuint64_t)SEQ * HD * 2};
    cuuint32_t box[3] = {64, rows, 1};
    cuuint32_t es[3] = {1, 1, 1};
    f(m, CU_TENSOR_MAP_DATA_TYPE_BFLOAT16, 3, p, dims, strides, box, es, CU_TENSOR_MAP_INTERLEAVE_NONE,
      CU_TENSOR_MAP_SWIZZLE_128B, CU_TENSOR_MAP_L2_PROMOTION_NONE, CU_TENSOR_MAP_FLOAT_OOB_FILL_NONE);
}

}

extern "C" void kernel_launch(void* const* d_in, const int* in_sizes, int n_in, void* d_out, int out_size) {
    (void)in_sizes; (void)n_in; (void)out_size;
    static EncodeFn enc = nullptr;
    static float* scratch = nullptr;
    if (!enc) {
        void* fn = nullptr;
        cudaDriverEntryPointQueryResult st;
        cudaGetDriverEntryPoint("cuTensorMapEncodeTiled", &fn, cudaEnableDefault, &st);
        enc = (EncodeFn)fn;
        cudaGetSymbolAddress((void**)&scratch, g_scratch);
        cudaFuncSetAttribute(attn_kernel, cudaFuncAttributeMaxDynamicSharedMemorySize, SM_TOTAL);
    }
    Maps maps;
    make_map(enc, &maps.q, d_in[0], 64);
    make_map(enc, &maps.k, d_in[1], 64);
    make_map(enc, &maps.v, d_in[2], 64);
    make_map(enc, &maps.o, d_out, 64);
    make_map(enc, &maps.o62, d_out, 64 - FAST_G);
    make_map(enc, &maps.k32, d_in[1], 32);
    make_map(enc, &maps.v32, d_in[2], 32);
    attn_kernel<<<128, 384, SM_TOTAL>>>(maps, (const __nv_bfloat16*)d_in[0], (const __nv_bfloat16*)d_in[1],
                                        (const __nv_bfloat16*)d_in[2], (const int*)d_in[3], (const int*)d_in[4],
                                        (__nv_bfloat16*)d_out, scratch);
}
```

```cpp
#include <cuda_runtime.h>
#include <cuda.h>
#include <cuda_bf16.h>
#include <stdint.h>

namespace {

constexpr int NH = 16, SEQ = 2048, HD = 256;
constexpr int FAST_W = 32, FAST_G = 2;

constexpr uint32_t base = 1024;
constexpr uint32_t SM_X = 196608;
constexpr uint32_t SM_QG = SM_X + 24576;
constexpr uint32_t SM_KG = SM_QG + 1024;
constexpr uint32_t SM_VG = SM_KG + 1024;
constexpr uint32_t SM_PT = SM_VG + 1152;
constexpr uint32_t SM_EX = SM_PT + 1280;
constexpr uint32_t SM_ML = SM_EX + 256;
constexpr uint32_t SM_BAR = SM_ML + 1024;
constexpr int B_FULL = 0, B_REL = 56, B_SF = 72, B_GV = 88, B_GR = 93, B_XF = 94, B_XV = 98;
constexpr uint32_t SM_TOTAL = base + SM_BAR + 102 * 8;
static_assert(SM_TOTAL <= 232448, "shared memory");
constexpr uint32_t bars = base + SM_BAR;

struct Maps { CUtensorMap k, v, q, k32, v32, o, o62, o16; };

enum { K0, V0, Q0, K1, V1, Q1, K2, V2, Q2, K3, V3, Q3, K4, V4 };
#define PREV_LIST -2, -4, -3, -1, -5, Q0, -6, K0, Q1, V0, V1, K2, K1, Q2
__host__ __device__ constexpr int prev_of(int b) {
    constexpr int prev[14] = {PREV_LIST};
    return prev[b];
}
__host__ __device__ constexpr int slot_of(int b) {
    while (prev_of(b) >= 0) b = prev_of(b);
    return -1 - prev_of(b);
}
__host__ __device__ constexpr uint64_t slot_tab() {
    uint64_t r = 0;
    for (int i = 0; i < 14; i++) r |= (uint64_t)slot_of(i) << (4 * i);
    return r;
}
constexpr uint64_t TAB_SLOT = slot_tab();

struct Load {
    uint32_t dst, full, col, map;
    uint32_t hard, soft;
    int deadline, row;
};
struct alignas(64) Sched {
    Load ld[52];
    uint16_t st[12];
};

constexpr int POLL_GATE = 4 * V4;

constexpr int PART = 136, DSTP = 12 * PART, HEADP = 4 * DSTP + 32;
__device__ __align__(128) float g_scratch[NH * HEADP];

#define DEVINL __device__ __forceinline__

DEVINL void mbar_init(uint32_t b, uint32_t c) { asm volatile("mbarrier.init.shared::cta.b64 [%0], %1;" ::"r"(b), "r"(c) : "memory"); }
DEVINL void mbar_expect(uint32_t b, uint32_t tx) { asm volatile("mbarrier.arrive.expect_tx.shared::cta.b64 _, [%0], %1;" ::"r"(b), "r"(tx) : "memory"); }
DEVINL void mbar_arrive(uint32_t b) { asm volatile("mbarrier.arrive.shared::cta.b64 _, [%0];" ::"r"(b) : "memory"); }
DEVINL void mbar_wait(uint32_t b) {
    asm volatile(
        "{\n.reg .pred p;\n"
        "WAIT_%=:\n"
        "mbarrier.try_wait.parity.shared::cta.b64 p, [%0], 0;\n"
        "@!p bra WAIT_%=;\n"
        "}\n" ::"r"(b) : "memory");
}
DEVINL bool mbar_test(uint32_t b) {
    uint32_t ok;
    asm volatile("{.reg .pred p; mbarrier.test_wait.parity.shared::cta.b64 p, [%1], 0; selp.u32 %0,1,0,p;}" : "=r"(ok) : "r"(b) : "memory");
    return ok != 0;
}
DEVINL uint32_t now_ns() { uint32_t t; asm volatile("mov.u32 %0, %globaltimer_lo;" : "=r"(t)); return t; }
DEVINL void tma_load3(uint32_t dst, const CUtensorMap* m, uint32_t bar, int c0, int c1, int c2, uint64_t pol) {
    asm volatile("cp.async.bulk.tensor.3d.shared::cluster.global.mbarrier::complete_tx::bytes.L2::cache_hint [%0], [%1, {%3,%4,%5}], [%2], %6;"
                 ::"r"(dst), "l"(m), "r"(bar), "r"(c0), "r"(c1), "r"(c2), "l"(pol) : "memory");
}
DEVINL void tma_store3(const CUtensorMap* m, uint32_t src, int c0, int c1, int c2) {
    asm volatile("cp.async.bulk.tensor.3d.global.shared::cta.bulk_group [%0, {%2,%3,%4}], [%1];"
                 ::"l"(m), "r"(src), "r"(c0), "r"(c1), "r"(c2) : "memory");
}
DEVINL void stsm4(uint32_t a, uint32_t r0, uint32_t r1, uint32_t r2, uint32_t r3) {
    asm volatile("stmatrix.sync.aligned.m8n8.x4.shared.b16 [%0], {%1,%2,%3,%4};" ::"r"(a), "r"(r0), "r"(r1), "r"(r2), "r"(r3) : "memory");
}
DEVINL uint32_t pack_bf16(float lo, float hi) {
    uint32_t r;
    asm("cvt.rn.bf16x2.f32 %0, %1, %2;" : "=r"(r) : "f"(hi), "f"(lo));
    return r;
}
DEVINL float ex2(float x) { float y; asm("ex2.approx.ftz.f32 %0, %1;" : "=f"(y) : "f"(x)); return y; }

DEVINL bool elect_one() {
    uint32_t p;
    asm volatile("{.reg .pred P; elect.sync _|P, 0xffffffff; selp.u32 %0, 1, 0, P;}" : "=r"(p));
    return p != 0;
}
DEVINL void wg_fence() { asm volatile("wgmma.fence.sync.aligned;" ::: "memory"); }
DEVINL void wg_commit() { asm volatile("wgmma.commit_group.sync.aligned;" ::: "memory"); }
template <int N> DEVINL void wg_wait() { asm volatile("wgmma.wait_group.sync.aligned %0;" ::"n"(N) : "memory"); }
template <int N> DEVINL void reg_fence(float (&d)[N]) {
#pragma unroll
    for (int i = 0; i < N; i++) asm volatile("" : "+f"(d[i])::"memory");
}
DEVINL uint64_t desc_at(uint32_t addr, uint32_t off) {
    uint64_t d;
    asm("mov.b64 %0, {%1, 0x40000040};" : "=l"(d) : "r"(((addr >> 4) | (1u << 16)) + off));
    return d;
}
constexpr uint32_t DESC0 = (base >> 4) | (1u << 16);
DEVINL uint64_t desc_lo(uint32_t lo, uint32_t hi) {
    uint64_t d;
    asm("mov.b64 %0, {%1, %2};" : "=l"(d) : "r"(lo), "r"(hi));
    return d;
}
DEVINL uint64_t desc_g(uint32_t addr) {
    uint64_t d;
    asm("mov.b64 %0, {%1, 2};" : "=l"(d) : "r"((addr >> 4) | (2u << 16)));
    return d;
}
#define ACC32 "{%0,%1,%2,%3,%4,%5,%6,%7,%8,%9,%10,%11,%12,%13,%14,%15,%16,%17,%18,%19,%20,%21,%22,%23,%24,%25,%26,%27,%28,%29,%30,%31}"
#define OPS32(c, d) c(d[0]), c(d[1]), c(d[2]), c(d[3]), c(d[4]), c(d[5]), c(d[6]), c(d[7]), c(d[8]), c(d[9]), c(d[10]), c(d[11]), \
    c(d[12]), c(d[13]), c(d[14]), c(d[15]), c(d[16]), c(d[17]), c(d[18]), c(d[19]), c(d[20]), c(d[21]), c(d[22]), c(d[23]),     \
    c(d[24]), c(d[25]), c(d[26]), c(d[27]), c(d[28]), c(d[29]), c(d[30]), c(d[31])
template <int TRANS_B>
DEVINL void wgmma_n64(float (&d)[32], uint32_t a0, uint32_t a1, uint32_t a2, uint32_t a3, uint64_t desc, bool acc) {
    if (acc)
        asm volatile("wgmma.mma_async.sync.aligned.m64n64k16.f32.bf16.bf16 " ACC32 ", {%32,%33,%34,%35}, %36, 1, 1, 1, %37;"
                     : OPS32("+f", d) : "r"(a0), "r"(a1), "r"(a2), "r"(a3), "l"(desc), "n"(TRANS_B));
    else
        asm volatile("wgmma.mma_async.sync.aligned.m64n64k16.f32.bf16.bf16 " ACC32 ", {%32,%33,%34,%35}, %36, 0, 1, 1, %37;"
                     : OPS32("=f", d) : "r"(a0), "r"(a1), "r"(a2), "r"(a3), "l"(desc), "n"(TRANS_B));
}
DEVINL void wgmma_n64_ss(float (&d)[32], uint64_t da, uint64_t db) {
    asm volatile("wgmma.mma_async.sync.aligned.m64n64k16.f32.bf16.bf16 " ACC32 ", %32, %33, 1, 1, 1, 0, 0;" : OPS32("+f", d) : "l"(da), "l"(db));
}
template <int TRANS_A>
DEVINL void wgmma_n8_ss(float (&d)[4], uint64_t da, uint64_t db) {
    asm volatile("wgmma.mma_async.sync.aligned.m64n8k16.f32.bf16.bf16 {%0,%1,%2,%3}, %4, %5, 1, 1, 1, %6, 0;"
                 : "+f"(d[0]), "+f"(d[1]), "+f"(d[2]), "+f"(d[3]) : "l"(da), "l"(db), "n"(TRANS_A));
}
DEVINL void sts2f(uint32_t a, float x, float y) { asm volatile("st.shared.v2.f32 [%0], {%1,%2};" ::"r"(a), "f"(x), "f"(y) : "memory"); }
DEVINL float4 lds4f(uint32_t a) {
    float4 r;
    asm volatile("ld.shared.v4.f32 {%0,%1,%2,%3}, [%4];" : "=f"(r.x), "=f"(r.y), "=f"(r.z), "=f"(r.w) : "r"(a) : "memory");
    return r;
}
DEVINL uint32_t or_xor(uint32_t acc, uint32_t x, uint32_t tag) {
    uint32_t r;
    asm("lop3.b32 %0, %1, %2, %3, 0xf6;" : "=r"(r) : "r"(acc), "r"(x), "r"(tag));
    return r;
}
DEVINL uint32_t tagged(float x, uint32_t tag) { return (__float_as_uint(x) & ~1u) | tag; }
DEVINL void st_rlx2(float* p, uint32_t a, uint32_t b) {
    asm volatile("st.relaxed.gpu.global.v2.u32 [%0], {%1,%2};" ::"l"(p), "r"(a), "r"(b) : "memory");
}
DEVINL uint2 ld_rlx2(const float* p) {
    uint2 r;
    asm volatile("ld.relaxed.gpu.global.v2.u32 {%0,%1}, [%2];" : "=r"(r.x), "=r"(r.y) : "l"(p) : "memory");
    return r;
}
DEVINL uint32_t ld_rlx(const float* p) {
    uint32_t r;
    asm volatile("ld.relaxed.gpu.global.u32 %0, [%1];" : "=r"(r) : "l"(p) : "memory");
    return r;
}

constexpr float SCALE_LOG2 = 0.0625f * 1.4426950408889634f;

__device__ __noinline__ void generic_path(const __nv_bfloat16* __restrict__ q, const __nv_bfloat16* __restrict__ k,
                                          const __nv_bfloat16* __restrict__ v, __nv_bfloat16* __restrict__ out,
                                          int window, int ng) {
    const int lane = threadIdx.x & 31, warp = threadIdx.x >> 5;
    const int h = blockIdx.x >> 3, c = blockIdx.x & 7;
    for (int r = warp; r < 256; r += 15) {
        const int row = c * 256 + r;
        float qv[8], acc[8];
        {
            uint4 u = *(const uint4*)(q + ((size_t)h * SEQ + row) * HD + lane * 8);
            const __nv_bfloat16* p = (const __nv_bfloat16*)&u;
            for (int i = 0; i < 8; i++) { qv[i] = __bfloat162float(p[i]); acc[i] = 0.f; }
        }
        float m = -INFINITY, l = 0.f;
        for (int j = 0; j < SEQ; j++) {
            const long long dist = (long long)row - j;
            const bool ok = (dist <= window && dist >= -(long long)window) || row < ng || j < ng;
            float s = -1e9f;
            if (ok) {
                uint4 u = *(const uint4*)(k + ((size_t)h * SEQ + j) * HD + lane * 8);
                const __nv_bfloat16* p = (const __nv_bfloat16*)&u;
                s = 0.f;
                for (int i = 0; i < 8; i++) s += qv[i] * __bfloat162float(p[i]);
                for (int o = 16; o > 0; o >>= 1) s += __shfl_xor_sync(0xffffffffu, s, o);
                s *= 0.0625f;
            }
            const float mn = fmaxf(m, s);
            const float a = __expf(m - mn), p = __expf(s - mn);
            m = mn;
            l = l * a + p;
            if (p != 0.f || a != 1.f) {
                uint4 u = *(const uint4*)(v + ((size_t)h * SEQ + j) * HD + lane * 8);
                const __nv_bfloat16* pv = (const __nv_bfloat16*)&u;
                for (int i = 0; i < 8; i++) acc[i] = acc[i] * a + p * __bfloat162float(pv[i]);
            }
        }
        const float inv = 1.f / l;
        uint4 o;
        o.x = pack_bf16(acc[0] * inv, acc[1] * inv); o.y = pack_bf16(acc[2] * inv, acc[3] * inv);
        o.z = pack_bf16(acc[4] * inv, acc[5] * inv); o.w = pack_bf16(acc[6] * inv, acc[7] * inv);
        *(uint4*)(out + ((size_t)h * SEQ + row) * HD + lane * 8) = o;
    }
}

DEVINL void consumer(const Maps& maps, __nv_bfloat16* __restrict__ out, const int wg, const int warp, const int lane, const int h,
                     const int q_first, const int step) {
    const int g = lane >> 2, cq = lane & 3;
    const int lrow = warp * 16 + (lane & 7) + ((lane >> 3) & 1) * 8;
    const int lcol = lane >> 4;
    const int dd = warp * 16 + g - 2 * cq;
    const bool has_diag = (unsigned)(g - 2 * cq) < 2u;
    mbar_wait(bars + 8 * B_GR);
#pragma unroll 1
    for (int t = wg; t < 4; t += 2) {
        const int q0 = q_first + step * t;
        const int shL = step < 0 ? 12 : 0, shU = 12 - shL;
        const uint32_t fb = bars + 8 * (B_FULL + 12 * t);
        const uint32_t slots = (uint32_t)(TAB_SLOT >> (12 * t));
        uint32_t oV1 = ((slots >> (4 + shL)) & 7u) * 2048u + DESC0, oV2 = ((slots >> (4 + shU)) & 7u) * 2048u + DESC0;
        uint32_t sbar = bars + 8 * (B_SF + t * 4);
        const int srow = (lrow + (q0 == 0 ? 64 - FAST_G : 0)) & 63;
        uint32_t sta[4];
#pragma unroll
        for (int i = 0; i < 4; i++) {
            sta[i] = base + ((slots >> (t == 3 ? 8 : 4)) & 7u) * 32768u + srow * 128 + (((2 * i + lcol) ^ (srow & 7)) << 4);
            asm volatile("" : "+r"(sta[i]));
        }
        uint32_t xoff = t == 3 ? 0u : SM_X - 8192u - ((slots >> 4) & 7u) * 32768u;
        uint32_t src3 = base + slot_of(Q3) * 32768 + warp * 2048, row3 = q0 + warp * 16;
        const CUtensorMap* map3 = &maps.o16;
        char* dst3 = (char*)(out + ((size_t)h * SEQ + q0 + warp * 16 + (lane >> 3)) * HD) + 384 + (lane & 7) * 16;
        uint32_t lds3 = src3 + 3 * 8192 + (lane >> 3) * 128 + (((lane & 7) ^ (lane >> 3)) << 4);
        asm volatile("" : "+r"(xoff), "+r"(src3), "+r"(row3), "+l"(map3), "+l"(dst3), "+r"(lds3));
        asm volatile("" : "+r"(oV1), "+r"(oV2), "+r"(sbar));
        uint32_t pL[16], pU[16], pg[2];
        float lsum[2];
        {
            const uint32_t rb = bars + 8 * (B_REL + 3 * t);
            uint32_t lowm[9][2];
#pragma unroll
            for (int k = 0; k < 9; k++)
#pragma unroll
                for (int e = 0; e < 2; e++)
                    asm volatile("shr.s32 %0, %1, 31;" : "=r"(lowm[k][e]) : "r"(dd - 1 - (8 * (k - 1) + e)));
            uint32_t lowp[9];
#pragma unroll
            for (int k = 0; k < 9; k++) asm volatile("lop3.b32 %0, %1, %2, 0xffff0000, 0xf8;" : "=r"(lowp[k]) : "r"(lowm[k][0]), "r"(lowm[k][1]));
            float sL[32], sU[32], sg[4];
#pragma unroll
            for (int i = 0; i < 32; i++) sL[i] = sU[i] = 0.f;
            sg[0] = sg[1] = sg[2] = sg[3] = 0.f;
            reg_fence(sL); reg_fence(sU); reg_fence(sg);
            uint64_t dQ = desc_at(base, ((slots >> 8) & 7u) * 2048u), dKG = desc_g(base + SM_KG);
            uint64_t dKL = desc_at(base, ((slots >> shL) & 7u) * 2048u), dKU = desc_at(base, ((slots >> shU) & 7u) * 2048u);
#pragma unroll 1
            for (int ch = 0; ch < 4; ch++) {
                mbar_wait(fb + 8 * ch);
                mbar_wait(fb + 8 * (12 + ch));
                mbar_wait(fb + 8 * (8 + ch));
                wg_fence();
#pragma unroll
                for (int ks = 0; ks < 4; ks++) {
                    wgmma_n8_ss<0>(sg, dQ + ks * 2, dKG + ks * 4);
                    wgmma_n64_ss(sL, dQ + ks * 2, dKL + ks * 2);
                    wgmma_n64_ss(sU, dQ + ks * 2, dKU + ks * 2);
                }
                wg_commit();
                if (t != 0) mbar_wait(fb + 8 * (4 + ch));
                dQ += 512; dKL += 512; dKU += 512; dKG += 16;
            }
            wg_wait<0>();
            reg_fence(sL); reg_fence(sU); reg_fence(sg);
#define NI "0fFF800000;"
            asm volatile("{\n.reg .pred p, q;\nsetp.eq.s32 p, %39, 3;\n@p bra.uni EDGE1_%=;\n"
                         "elect.sync _|q, 0xffffffff;\n@q mbarrier.arrive.shared::cta.b64 _, [%40];\n"
                         "@q mbarrier.arrive.shared::cta.b64 _, [%40 + 16];\n@q mbarrier.arrive.shared::cta.b64 _, [%40 + 24];\n"
                         "setp.ne.s32 p, %39, 0;\n@p bra.uni EDGE1_%=;\n"
                         "V0A_%=:\nmbarrier.try_wait.parity.shared::cta.b64 p, [%41], 0;\n@!p bra V0A_%=;\n"
                         "V0B_%=:\nmbarrier.try_wait.parity.shared::cta.b64 p, [%41 + 8], 0;\n@!p bra V0B_%=;\n"
                         "V0C_%=:\nmbarrier.try_wait.parity.shared::cta.b64 p, [%41 + 16], 0;\n@!p bra V0C_%=;\n"
                         "V0D_%=:\nmbarrier.try_wait.parity.shared::cta.b64 p, [%41 + 24], 0;\n@!p bra V0D_%=;\n"
                         "setp.ne.s32 p, %36, 0;\n@p bra.uni EDGE0_%=;\nsetp.eq.s32 q, %37, 0;\n"
                         "mov.f32 %0, " NI "mov.f32 %1, " NI "mov.f32 %2, " NI "mov.f32 %3, " NI "mov.f32 %4, " NI "mov.f32 %5, " NI
                         "mov.f32 %6, " NI "mov.f32 %7, " NI "mov.f32 %8, " NI "mov.f32 %9, " NI "mov.f32 %10, " NI "mov.f32 %11, " NI
                         "mov.f32 %12, " NI "mov.f32 %13, " NI "mov.f32 %14, " NI "mov.f32 %15, " NI "@q mov.f32 %16, " NI
                         "@q mov.f32 %17, " NI "@q mov.f32 %18, " NI "@q mov.f32 %19, " NI "\nEDGE0_%=:\n"
                         "setp.ne.s32 p, %36, %38;\n@p bra.uni EDGE1_%=;\n"
                         "mov.f32 %20, " NI "mov.f32 %21, " NI "mov.f32 %22, " NI "mov.f32 %23, " NI "mov.f32 %24, " NI "mov.f32 %25, " NI
                         "mov.f32 %26, " NI "mov.f32 %27, " NI "mov.f32 %28, " NI "mov.f32 %29, " NI "mov.f32 %30, " NI "mov.f32 %31, " NI
                         "mov.f32 %32, " NI "mov.f32 %33, " NI "mov.f32 %34, " NI "mov.f32 %35, " NI "\nEDGE1_%=:\n}"
                         : "+f"(sL[0]), "+f"(sL[1]), "+f"(sL[2]), "+f"(sL[3]), "+f"(sL[4]), "+f"(sL[5]), "+f"(sL[6]), "+f"(sL[7]),
                           "+f"(sL[8]), "+f"(sL[9]), "+f"(sL[10]), "+f"(sL[11]), "+f"(sL[12]), "+f"(sL[13]), "+f"(sL[14]), "+f"(sL[15]),
                           "+f"(sL[16]), "+f"(sL[17]), "+f"(sL[18]), "+f"(sL[19]),
                           "+f"(sU[16]), "+f"(sU[17]), "+f"(sU[18]), "+f"(sU[19]), "+f"(sU[20]), "+f"(sU[21]), "+f"(sU[22]), "+f"(sU[23]),
                           "+f"(sU[24]), "+f"(sU[25]), "+f"(sU[26]), "+f"(sU[27]), "+f"(sU[28]), "+f"(sU[29]), "+f"(sU[30]), "+f"(sU[31])
                         : "r"(q0), "r"(cq), "n"(SEQ - 64), "r"(t), "r"(rb), "r"(bars + 8 * (B_FULL + 4 * V0)) : "memory");
#pragma unroll
            for (int r = 0; r < 2; r++) {
                float x[19];
#pragma unroll
                for (int i = 0; i < 8; i++)
#pragma unroll
                    for (int e = 0; e < 2; e++) {
                        const uint32_t mk = lowm[i - r + 1][e];
                        x[2 * i + e] = __uint_as_float((__float_as_uint(sL[4 * i + 2 * r + e]) & mk) | (__float_as_uint(sU[4 * i + 2 * r + e]) & ~mk));
                    }
                float z[4];
#pragma unroll
                for (int w = 0; w < 4; w++) z[w] = (g & 1) ? sU[8 * w + 6 * r + 1] : sU[8 * w + 6 * r];
                const float zz = warp < 2 ? (warp == 0 ? z[0] : z[1]) : (warp == 2 ? z[2] : z[3]);
                x[16] = has_diag ? zz : -INFINITY;
                x[17] = cq == 0 ? sg[2 * r] : -INFINITY;
                x[18] = cq == 0 ? sg[2 * r + 1] : -INFINITY;
                float u[4];
#pragma unroll
                for (int i = 0; i < 4; i++) u[i] = fmaxf(fmaxf(x[4 * i], x[4 * i + 1]), fmaxf(x[4 * i + 2], x[4 * i + 3]));
                float m = fmaxf(fmaxf(fmaxf(u[0], u[1]), fmaxf(u[2], u[3])), fmaxf(x[16], fmaxf(x[17], x[18])));
                const float m1 = __shfl_xor_sync(0xffffffffu, m, 1), m2 = __shfl_xor_sync(0xffffffffu, m, 2), m3 = __shfl_xor_sync(0xffffffffu, m, 3);
                m = fmaxf(fmaxf(m, m1), fmaxf(m2, m3));
                const float mc = -m * SCALE_LOG2;
#pragma unroll
                for (int i = 18; i >= 0; i--) x[i] = ex2(fmaf(x[i], SCALE_LOG2, mc));
#pragma unroll
                for (int i = 0; i < 4; i++) u[i] = (x[4 * i] + x[4 * i + 1]) + (x[4 * i + 2] + x[4 * i + 3]);
                lsum[r] = ((u[0] + u[1]) + (u[2] + u[3])) + (x[16] + (x[17] + x[18]));
                const uint32_t pd = pack_bf16(x[16], 0.f) << (16 * (g & 1));
                pg[r] = pack_bf16(x[17], x[18]);
#pragma unroll
                for (int i = 0; i < 8; i++) {
                    const uint32_t mk = lowp[i - r + 1];
                    const uint32_t pp = pack_bf16(x[2 * i], x[2 * i + 1]);
                    pL[2 * i + r] = pp & mk;
                    pU[2 * i + r] = pp & ~mk;
                    if ((i & 1) == r) pU[2 * i + r] |= (warp == (i >> 1)) ? pd : 0u;
                }
            }
#pragma unroll
            for (int i = 0; i < 16; i++) asm volatile("" : "+r"(pL[i]), "+r"(pU[i]));
        }
        const uint64_t dV1 = desc_lo(oV1, 0x40000040u), dV2 = desc_lo(oV2, 0x40000040u), dVG = desc_g(base + SM_VG);
        float oa[32], ob[32], inv0, inv1;
        auto mma = [&](float (&o)[32], int ch, bool landed) {
            if (!landed) mbar_wait(fb + 8 * (16 + ch));
            wg_fence();
            wgmma_n64<1>(o, pg[0], pg[1], 0u, 0u, dVG + ch * 16, false);
#pragma unroll
            for (int kk = 0; kk < 4; kk++)
                wgmma_n64<1>(o, pL[4 * kk], pL[4 * kk + 1], pL[4 * kk + 2], pL[4 * kk + 3], dV1 + (ch * 512 + kk * 128), true);
#pragma unroll
            for (int kk = 0; kk < 4; kk++)
                wgmma_n64<1>(o, pU[4 * kk], pU[4 * kk + 1], pU[4 * kk + 2], pU[4 * kk + 3], dV2 + (ch * 512 + kk * 128), true);
            wg_commit();
        };
        auto stage = [&](float (&o)[32], int ch) {
            reg_fence(o);
            if (ch == 0 && t != 3) asm volatile("bar.sync %0, 128;" ::"r"(2 + wg) : "memory");
            if (ch == 1) {
                if (t == 1 || t == 2) mbar_wait(bars + 8 * (B_XF + t - 1));
#pragma unroll
                for (int i = 0; i < 4; i++) sta[i] += xoff;
            }
#pragma unroll
            for (int i = 0; i < 4; i++)
                stsm4(sta[i] + ch * 8192, pack_bf16(o[8 * i] * inv0, o[8 * i + 1] * inv0), pack_bf16(o[8 * i + 2] * inv1, o[8 * i + 3] * inv1),
                      pack_bf16(o[8 * i + 4] * inv0, o[8 * i + 5] * inv0), pack_bf16(o[8 * i + 6] * inv1, o[8 * i + 7] * inv1));
        };
        auto done = [&](int ch) {
            if (t != 3) {
                asm volatile("fence.proxy.async.shared::cta;" ::: "memory");
                __syncwarp();
                if (elect_one()) mbar_arrive(sbar + 8 * ch);
            }
        };
        auto done3 = [&](int ch) {
            if (t == 3) {
                asm volatile("fence.proxy.async.shared::cta;" ::: "memory");
                __syncwarp();
                if (elect_one()) tma_store3(map3, src3 + ch * 8192, ch * 64, row3, h);
            }
        };
        mma(oa, 0, false);
        if (t != 3) mbar_wait(bars + 8 * (B_GV + t));
        else asm volatile("bar.sync %0, 128;" ::"r"(2 + wg) : "memory");
        lsum[0] += __shfl_xor_sync(0xffffffffu, lsum[0], 1);
        lsum[1] += __shfl_xor_sync(0xffffffffu, lsum[1], 1);
        lsum[0] += __shfl_xor_sync(0xffffffffu, lsum[0], 2);
        lsum[1] += __shfl_xor_sync(0xffffffffu, lsum[1], 2);
        asm volatile("rcp.approx.ftz.f32 %0, %1;" : "=f"(inv0) : "f"(lsum[0]));
        asm volatile("rcp.approx.ftz.f32 %0, %1;" : "=f"(inv1) : "f"(lsum[1]));
        mma(ob, 1, false);
        bool landed = mbar_test(fb + 8 * 18);
        wg_wait<1>(); stage(oa, 0); done(0); mma(oa, 2, landed); done3(0);
        landed = mbar_test(fb + 8 * 19);
        wg_wait<1>(); stage(ob, 1); done(1); mma(ob, 3, landed); done3(1);
        wg_wait<1>(); stage(oa, 2); done(2); done3(2);
        wg_wait<0>();
        if (t != 3 && elect_one()) { mbar_arrive(bars + 8 * (B_REL + 3 * t + 1)); mbar_arrive(bars + 8 * (B_GV + t + 1)); }
        stage(ob, 3); done(3);
        if (t == 3) {
            __syncwarp();
            float4 z[4];
#pragma unroll
            for (int i = 0; i < 4; i++) z[i] = lds4f((lds3 ^ ((i & 1) * 64)) + i * 512);
#pragma unroll
            for (int i = 0; i < 4; i++) *(float4*)(dst3 + i * 2048) = z[i];
            asm volatile("cp.async.bulk.commit_group;" ::: "memory");
            asm volatile("cp.async.bulk.wait_group.read 0;" ::: "memory");
        }
    }
}

__global__ void __launch_bounds__(480, 1)
attn_kernel(const __grid_constant__ Maps maps, const __grid_constant__ Sched sched, const __nv_bfloat16* __restrict__ q,
            const __nv_bfloat16* __restrict__ k, const __nv_bfloat16* __restrict__ v, const int* __restrict__ p_window,
            const int* __restrict__ p_ng, __nv_bfloat16* __restrict__ out, float* __restrict__ scratch) {
    const uint32_t t_start = now_ns();
    const int lane = threadIdx.x & 31;
    const int h = blockIdx.x >> 3, c = blockIdx.x & 7;
    const bool rev = c & 1;
    const int step = rev ? -64 : 64;
    const int q_first = c * 256 + (rev ? 192 : 0);

    uint64_t pol;
    asm volatile("createpolicy.fractional.L2::evict_first.b64 %0, 1.0;" : "=l"(pol));

    static_assert(slot_of(K1) == 0, "prologue");
    if (threadIdx.x >= 384 && threadIdx.x < 416) {
        if (elect_one()) {
#pragma unroll
            for (int ch = 0; ch < 4; ch++) mbar_init(bars + 8 * (4 * K1 + ch), 1);
#pragma unroll
            for (int ch = 0; ch < 4; ch++) {
                mbar_expect(bars + 8 * (4 * K1 + ch), 8192);
                tma_load3(base + ch * 8192, &maps.k, bars + 8 * (4 * K1 + ch), ch * 64, c * 256 + 96 - step, h, pol);
            }
        }
        __syncwarp();
    }
    const int warp = __shfl_sync(0xffffffffu, threadIdx.x >> 5, 0);
    if (elect_one()) {
        if (warp < 8) {
            if (warp < 7) asm volatile("prefetch.tensormap [%0];" ::"l"(&maps.v + warp) : "memory");
#pragma unroll
            for (int i = 0; i < 5; i++) mbar_init(bars + 8 * (B_FULL + 16 + warp * 5 + i), 1);
#pragma unroll
            for (int i = 0; i < 2; i++) mbar_init(bars + 8 * (B_SF + warp * 2 + i), 4);
        } else if (warp < 12) {
            const int j = warp - 8;
            mbar_init(bars + 8 * (B_REL + 3 * j), j == 0 ? 8 : 12);
            mbar_init(bars + 8 * (B_REL + 3 * j + 1), 5);
            mbar_init(bars + 8 * (B_XF + j), 1);
            mbar_init(bars + 8 * (B_XV + j), 1);
            mbar_init(bars + 8 * (B_REL + 3 * j + 2), 4);
            mbar_init(bars + 8 * (B_GV + j), j == 0 ? 4 : 8);
#pragma unroll
            for (int i = 0; i < 3; i++) mbar_init(bars + 8 * (B_FULL + 3 * j + i), 1);
        } else if (warp == 13) {
            mbar_init(bars + 8 * (B_REL + K4), 12);
            mbar_init(bars + 8 * B_GR, 4);
        }
    }
    __syncthreads();
    int window, ng;
    uint4 gx, gy;
    uint32_t epoch;
    if ((warp | 2) != 14) {
        if (warp >= 8 && warp < 12) {
            const size_t off = ((size_t)h * SEQ + (warp & 1)) * HD + lane * 8;
            gx = __ldg((const uint4*)((warp & 2 ? v : k) + off));
            gy = __ldg((const uint4*)(q + off));
            epoch = ld_rlx(scratch + h * HEADP + 4 * DSTP);
        }
        asm volatile("ld.global.nc.u32 %0, [%1];" : "=r"(window) : "l"(p_window));
        asm volatile("ld.global.nc.u32 %0, [%1];" : "=r"(ng) : "l"(p_ng));
        static_assert(sizeof(Sched) <= 27 * 64, "touch");
        const uint32_t* const tp = (const uint32_t*)&sched + 16 + 32 * (warp - (warp > 12));
        if ((tp[0] & tp[16]) == 0xffffffffu) __trap();
    } else {
        const int mid = c * 256 + 96, sgn = rev ? -1 : 1;
        int p = (warp >> 1) & 1;
#pragma unroll 1
        for (int seg = 0; seg < 3; seg++) {
            const int pe = seg == 0 ? 8 : seg == 1 ? 20 : 52;
#pragma unroll 1
            for (; p < pe; p += 2) {
                const Load e = sched.ld[p];
                const CUtensorMap* const map = (const CUtensorMap*)((const char*)&maps + e.map);
                const int row = mid + sgn * e.row;
                if (e.hard) mbar_wait(e.hard);
                while ((int)(now_ns() - t_start) < e.deadline && !mbar_test(e.soft)) {}
                if (elect_one()) {
                    mbar_expect(e.full, 8192);
                    tma_load3(e.dst, map, e.full, e.col, row & (SEQ - 1), h, pol);
                    if (e.map >= 3 * 128) tma_load3(e.dst + 4096, map, e.full, e.col, row + 32, h, pol);
                }
            }
            if (seg == 0) {
                asm volatile("ld.global.nc.u32 %0, [%1];" : "=r"(window) : "l"(p_window));
                asm volatile("ld.global.nc.u32 %0, [%1];" : "=r"(ng) : "l"(p_ng));
            } else {
                int bad;
                asm volatile("{.reg .b32 a, b; xor.b32 a, %1, %3; xor.b32 b, %2, %4; or.b32 %0, a, b;}"
                             : "=r"(bad) : "r"(window), "r"(ng), "n"(FAST_W), "n"(FAST_G));
                if (__shfl_sync(0xffffffffu, bad, 0) != 0) break;
            }
        }
    }

    if (window != FAST_W || ng != FAST_G) {
#pragma unroll 1
        for (int i = 0; i < 28; i++)
            if ((i >> 2) != Q1) mbar_wait(bars + 8 * i);
        generic_path(q, k, v, out, window, ng);
        return;
    }

    if (warp < 8) {
        asm volatile("setmaxnreg.inc.sync.aligned.u32 144;");
        consumer(maps, out, warp >> 2, warp & 3, lane, h, q_first, step);
    } else if (warp < 12) {
        asm volatile("setmaxnreg.dec.sync.aligned.u32 96;");
        const int w = warp & 3, tid = threadIdx.x - 256;
        const int g = lane >> 2, cq = lane & 3;
        const uint32_t tag = (epoch + 1u) & 1u;
        float* const part = scratch + h * HEADP;
        {
            const uint32_t a = base + SM_QG + lane * 32 + (w & 1) * 16;
            asm volatile("st.shared.v4.u32 [%0], {%1,%2,%3,%4};" ::"r"(a + 1024 + (w & 2) * 512), "r"(gx.x), "r"(gx.y), "r"(gx.z), "r"(gx.w) : "memory");
            asm volatile("st.shared.v4.u32 [%0], {%1,%2,%3,%4};" ::"r"(a), "r"(gy.x), "r"(gy.y), "r"(gy.z), "r"(gy.w) : "memory");
            asm volatile("st.shared.u32 [%0], %1;" ::"r"(base + SM_VG + 1024 + lane * 4), "r"(0u) : "memory");
            asm volatile("fence.proxy.async.shared::cta;" ::: "memory");
            __syncwarp();
            if (elect_one()) {
                mbar_arrive(bars + 8 * B_GR);
                if (rev) { mbar_arrive(bars + 8 * B_REL); mbar_arrive(bars + 8 * B_GV); }
            }
            mbar_wait(bars + 8 * B_GR);
        }
        float og[4][4];
#pragma unroll
        for (int i = 0; i < 4; i++) { og[i][0] = og[i][1] = og[i][2] = og[i][3] = 0.f; }
        float m0 = -1e30f, m1 = -1e30f, l0 = 0.f, l1 = 0.f;
        const int koff = (w * 16 + g) * 2;
        const float* const src = part + (c >> 1) * DSTP;
        uint32_t mk = 0, lk = 0;
        int spins = 0;
#pragma unroll 1
        for (int j = rev; j < 5; j++) {
            const bool fin = j == 4 && !rev;
            const int jv = j < 4 ? j : 3;
            uint32_t vbar = bars + 8 * (B_FULL + 12 * jv + 4), oV = ((uint32_t)(TAB_SLOT >> (12 * jv + 4)) & 7u) * 2048u, pstep = 0;
            float e[4], a0 = 0.f, a1 = 0.f;
            uint32_t x[8];
            uint2 ml;
            auto fetch = [&]() {
                ml = ld_rlx2(src + min(lane & 15, 11) * PART + 128 + (lane >> 4) * 2);
#pragma unroll
                for (int i = 0; i < 8; i++) x[i] = ld_rlx(src + i * PART + koff + (cq >> 1) * 16 + (cq & 1));
            };
            if (!fin) {
                float st[4] = {0.f, 0.f, 0.f, 0.f};
                reg_fence(st);
                uint64_t dK = desc_at(base, ((uint32_t)(TAB_SLOT >> (12 * j)) & 7u) * 2048u), dQG = desc_g(base + SM_QG);
#pragma unroll 1
                for (int ch = 0; ch < 4; ch++) {
                    mbar_wait(bars + 8 * (B_FULL + 12 * j + ch));
                    wg_fence();
#pragma unroll
                    for (int ks = 0; ks < 4; ks++) wgmma_n8_ss<0>(st, dK + ks * 2, dQG + ks * 4);
                    wg_commit();
                    dK += 512; dQG += 16;
                }
                wg_wait<0>();
                reg_fence(st);
                if (elect_one()) mbar_arrive(bars + 8 * (B_REL + 3 * j));
#pragma unroll
                for (int i = 0; i < 4; i++) st[i] = __shfl_sync(0xffffffffu, st[i], lane & ~3);
                float t0 = fmaxf(st[0], st[2]), t1 = fmaxf(st[1], st[3]);
#pragma unroll
                for (int o = 4; o < 32; o <<= 1) {
                    t0 = fmaxf(t0, __shfl_xor_sync(0xffffffffu, t0, o));
                    t1 = fmaxf(t1, __shfl_xor_sync(0xffffffffu, t1, o));
                }
                if (lane == 0) sts2f(base + SM_EX + j * 32 + w * 8, t0, t1);
                asm volatile("bar.sync 1, 128;" ::: "memory");
                const float4 xa = lds4f(base + SM_EX + j * 32), xb = lds4f(base + SM_EX + j * 32 + 16);
                const float n0 = fmaxf(fmaxf(m0, fmaxf(xa.x, xa.z)), fmaxf(xb.x, xb.z)), n1 = fmaxf(fmaxf(m1, fmaxf(xa.y, xa.w)), fmaxf(xb.y, xb.w));
                a0 = ex2((m0 - n0) * SCALE_LOG2); a1 = ex2((m1 - n1) * SCALE_LOG2);
                m0 = n0; m1 = n1;
                e[0] = ex2((st[0] - n0) * SCALE_LOG2); e[1] = ex2((st[1] - n1) * SCALE_LOG2);
                e[2] = ex2((st[2] - n0) * SCALE_LOG2); e[3] = ex2((st[3] - n1) * SCALE_LOG2);
                l0 = l0 * a0 + (e[0] + e[2]); l1 = l1 * a1 + (e[1] + e[3]);
                float s0 = l0, s1 = l1;
#pragma unroll
                for (int o = 4; o < 32; o <<= 1) {
                    s0 += __shfl_xor_sync(0xffffffffu, s0, o);
                    s1 += __shfl_xor_sync(0xffffffffu, s1, o);
                }
                if (lane == 0) sts2f(base + SM_EX + 160 + w * 8, s0, s1);
            } else {
                asm volatile("bar.sync 1, 128;" ::: "memory");
                uint32_t bad;
#pragma unroll 1
                do {
                    const uint2 y0 = ld_rlx2(src + (8 + cq) * PART + koff), y1 = ld_rlx2(src + (8 + cq) * PART + koff + 16);
                    bad = or_xor(or_xor(or_xor(y0.x ^ tag, y0.y, tag), y1.x, tag), y1.y, tag);
                    e[0] = __uint_as_float(y0.x); e[1] = __uint_as_float(y0.y); e[2] = __uint_as_float(y1.x); e[3] = __uint_as_float(y1.y);
                    if (++spins > (1 << 22)) __trap();
                } while (__any_sync(0xffffffffu, bad & 1u));
#pragma unroll
                for (int i = 0; i < 4; i++) { og[i][0] = og[i][1] = og[i][2] = og[i][3] = 0.f; }
                vbar = bars + 8 * B_XV; oV = slot_of(V2) * 2048u; pstep = 16;
            }
            if (j < 4 || fin) {
                const uint32_t pa = base + SM_PT + cq * 256 + w * 64 + g * 2, p01 = pack_bf16(e[0], e[1]), p23 = pack_bf16(e[2], e[3]);
                asm volatile("{.reg .b16 a, b; mov.b32 {a, b}, %1; st.shared.b16 [%0], a; st.shared.b16 [%0 + 16], b;"
                             "mov.b32 {a, b}, %2; st.shared.b16 [%0 + 32], a; st.shared.b16 [%0 + 48], b;}" ::"r"(pa), "r"(p01), "r"(p23) : "memory");
#pragma unroll
                for (int i = 0; i < 4; i++) { og[i][0] *= a0; og[i][1] *= a1; og[i][2] *= a0; og[i][3] *= a1; }
            }
#pragma unroll
            for (int i = 0; i < 4; i++) reg_fence(og[i]);
            asm volatile("fence.proxy.async.shared::cta;" ::: "memory");
            asm volatile("bar.sync 1, 128;" ::: "memory");
            if (!fin) {
                const float4 ya = lds4f(base + SM_EX + 160), yb = lds4f(base + SM_EX + 176);
                const uint32_t mt = tagged((cq & 1) ? m1 : m0, tag), lt = tagged((cq & 1) ? (ya.y + ya.w) + (yb.y + yb.w) : (ya.x + ya.z) + (yb.x + yb.z), tag);
                if (j == 4) {
                    float* const dst = part + (8 + (c >> 1)) * PART;
                    st_rlx2(dst + cq * DSTP + koff, tagged(e[0], tag), tagged(e[1], tag));
                    st_rlx2(dst + cq * DSTP + koff + 16, tagged(e[2], tag), tagged(e[3], tag));
                    if (tid < 16) st_rlx2(dst + g * DSTP + 128 + cq * 2, mt, lt);
                } else {
                    mk = mt; lk = lt;
                    if (j == 3 && rev) { m0 = m1 = -1e30f; l0 = l1 = 0.f; continue; }
                }
            } else {
                mbar_wait(bars + 8 * (B_FULL + POLL_GATE));
                fetch();
            }
            const uint64_t dV = desc_at(base, oV);
            uint64_t dPT = desc_g(base + SM_PT);
#pragma unroll
            for (int ch = 0; ch < 4; ch++) {
                mbar_wait(vbar + 8 * ch);
                wg_fence();
#pragma unroll
                for (int kk = 0; kk < 4; kk++) wgmma_n8_ss<1>(og[ch], dV + (ch * 512 + kk * 128), dPT + kk * 4);
                dPT += pstep;
            }
            wg_commit();
            wg_wait<0>();
#pragma unroll
            for (int i = 0; i < 4; i++) reg_fence(og[i]);
            if (fin) {
                while (true) {
                    uint32_t bad = or_xor(ml.x ^ tag, ml.y, tag);
#pragma unroll
                    for (int i = 0; i < 8; i++) bad = or_xor(bad, x[i], tag);
                    if (!__any_sync(0xffffffffu, bad & 1u)) break;
                    if (++spins > (1 << 22)) __trap();
                    fetch();
                }
                if (c == 0 && tid == 0) *(volatile uint32_t*)(part + 4 * DSTP) = epoch + 1u;
                sts2f(base + SM_ML + tid * 8, __uint_as_float(ml.x), __uint_as_float(ml.y));
                __syncwarp();
                float4 z[6];
#pragma unroll
                for (int i = 0; i < 6; i++) z[i] = lds4f(base + SM_ML + w * 256 + (cq & 1) * 128 + i * 16);
                float M = fmaxf(z[0].x, z[0].z), L = 0.f, r = 0.f, u[4];
#pragma unroll
                for (int i = 1; i < 6; i++) M = fmaxf(M, fmaxf(z[i].x, z[i].z));
#pragma unroll
                for (int i = 5; i >= 0; i--) {
                    z[i].x = ex2((z[i].x - M) * SCALE_LOG2); z[i].z = ex2((z[i].z - M) * SCALE_LOG2);
                    L += z[i].x * z[i].y + z[i].z * z[i].w;
                }
#pragma unroll
                for (int i = 0; i < 4; i++) r += __uint_as_float(x[2 * i]) * z[i].x + __uint_as_float(x[2 * i + 1]) * z[i].z;
                const float wl[4] = {z[4].x, z[4].z, z[5].x, z[5].z};
                float wo[4];
#pragma unroll
                for (int i = 0; i < 4; i++) wo[i] = __shfl_xor_sync(0xffffffffu, wl[i], 1);
#pragma unroll
                for (int i = 0; i < 4; i++) {
                    const float* const ww = (i & 1) ? wo : wl;
                    u[i] = __shfl_sync(0xffffffffu, (og[0][i] * ww[0] + og[1][i] * ww[1]) + (og[2][i] * ww[2] + og[3][i] * ww[3]), lane & ~3);
                }
                r += cq < 2 ? (cq == 0 ? u[0] : u[1]) : (cq == 2 ? u[2] : u[3]);
                out[((size_t)h * SEQ + (cq & 1)) * HD + (c >> 1) * 64 + w * 16 + g + (cq >> 1) * 8] = __float2bfloat16(__fdividef(r, L));
                break;
            }
            if (elect_one()) mbar_arrive(bars + 8 * (B_GV + jv));
            if (jv == 3) {
                if (cq == 0) {
#pragma unroll
                    for (int ch = 0; ch < 4; ch++) {
                        st_rlx2(part + ch * DSTP + c * PART + koff, tagged(og[ch][0], tag), tagged(og[ch][1], tag));
                        st_rlx2(part + ch * DSTP + c * PART + koff + 16, tagged(og[ch][2], tag), tagged(og[ch][3], tag));
                    }
                }
                if (tid < 16) st_rlx2(part + g * DSTP + c * PART + 128 + cq * 2, mk, lk);
            }
        }
    } else if (warp == 13) {
        if (elect_one()) {
#pragma unroll 1
            for (int t = 0; t < 3; t++) {
                const int q0 = q_first + t * step;
                const CUtensorMap* m = q0 == 0 ? &maps.o62 : &maps.o;
                const int row = q0 == 0 ? FAST_G : q0;
                const uint32_t src = base + ((uint32_t)(TAB_SLOT >> (12 * t + 4)) & 7u) * 32768u;
                const uint2 sw = *(const uint2*)&sched.st[4 * t];
#pragma unroll
                for (int ch = 0; ch < 4; ch++) {
                    mbar_wait(bars + 8 * (B_SF + t * 4 + ch));
                    const uint32_t hold = ((ch & 2 ? sw.y : sw.x) >> (16 * (ch & 1))) & 0xffffu;
                    if (hold) mbar_wait(bars - 8 + hold);
                    tma_store3(m, (ch == 0 ? src : base + SM_X - 8192) + ch * 8192, ch * 64, row, h);
                    if (ch == 0) {
                        asm volatile("cp.async.bulk.commit_group;" ::: "memory");
                        asm volatile("cp.async.bulk.wait_group.read 0;" ::: "memory");
                        mbar_arrive(bars + 8 * (B_REL + 3 * t + 1));
                        if (t == 2 && !rev) {
                            const Load& e = sched.ld[48 + (c >> 1)];
                            mbar_wait(bars + 8 * (B_REL + V2));
                            while ((int)(now_ns() - t_start) < e.deadline && !mbar_test(e.soft)) {}
#pragma unroll 1
                            for (int i = 0; i < 4; i++) {
                                mbar_expect(bars + 8 * (B_XV + i), 8192);
                                tma_load3(base + slot_of(V2) * 32768 + i * 8192, &maps.v, bars + 8 * (B_XV + i), e.col, i * 512 + 224, h, pol);
                            }
                        }
                    }
                }
                asm volatile("cp.async.bulk.commit_group;" ::: "memory");
                asm volatile("cp.async.bulk.wait_group.read 0;" ::: "memory");
                mbar_arrive(bars + 8 * (B_XF + t));
            }
        }
    }
}

__global__ void __launch_bounds__(480, 1)
generic_kernel(const __nv_bfloat16* __restrict__ q, const __nv_bfloat16* __restrict__ k, const __nv_bfloat16* __restrict__ v,
               const int* __restrict__ p_window, const int* __restrict__ p_ng, __nv_bfloat16* __restrict__ out) {
    generic_path(q, k, v, out, *p_window, *p_ng);
}

typedef CUresult (*EncodeFn)(CUtensorMap*, CUtensorMapDataType, cuuint32_t, void*, const cuuint64_t*, const cuuint64_t*,
                             const cuuint32_t*, const cuuint32_t*, CUtensorMapInterleave, CUtensorMapSwizzle,
                             CUtensorMapL2promotion, CUtensorMapFloatOOBfill);

void make_map(EncodeFn f, CUtensorMap* m, void* p, unsigned rows) {
    cuuint64_t dims[3] = {HD, SEQ, NH};
    cuuint64_t strides[2] = {HD * 2, (cuuint64_t)SEQ * HD * 2};
    cuuint32_t box[3] = {64, rows, 1};
    cuuint32_t es[3] = {1, 1, 1};
    f(m, CU_TENSOR_MAP_DATA_TYPE_BFLOAT16, 3, p, dims, strides, box, es, CU_TENSOR_MAP_INTERLEAVE_NONE,
      CU_TENSOR_MAP_SWIZZLE_128B, CU_TENSOR_MAP_L2_PROMOTION_NONE, CU_TENSOR_MAP_FLOAT_OOB_FILL_NONE);
}

void make_sched(Sched* sc) {
    constexpr int TAU = 380, TOFF = -2100;
    constexpr int HARD = 12;
    const int blocks[14] = {K1, K0, Q0, V0, V1, K2, Q1, V2, K3, Q2, K4, V3, Q3, V4};
    auto full = [&](int p) { return B_FULL + 4 * blocks[p >> 2] + (p & 3); };
    int dl = TOFF;
    for (int p = 0; p < 56; p++) {
        const int blk = blocks[p >> 2], ch = p & 3, idx = blk / 3, type = blk % 3;
        const int tau = (blk <= V0 || blk >= K4) ? TAU / 2 : TAU;
        if (p >= 4) {
            const bool pair = p < 48;
            const int hard = (pair ? p | 1 : p) - HARD;
            Load& e = sc->ld[p - 4];
            e.dst = base + slot_of(blk) * 32768 + ch * 8192;
            e.full = bars + 8 * full(p);
            e.col = ch * 64;
            e.map = (blk <= V0 ? 3 + blk : type) * 128;
            e.hard = (ch < 2 && prev_of(blk) >= 0) ? bars + 8 * (B_REL + prev_of(blk)) : hard >= 0 ? bars + 8 * full(hard) : 0;
            e.soft = bars + 8 * full(pair ? (p & ~1) - 4 : blk == Q3 ? p - 3 : p - 1);
            e.deadline = pair ? dl - (p & 1) * tau + tau / 2 : blk == Q3 ? dl : dl + 170 + 20 * ch;
            e.row = 64 * idx - (type == 2 ? 96 : 128);
        }
        dl += tau;
    }
    const int hold[12] = {-1, 22, 25, 28, -1, 34, 37, 40, -1, 51, 52, 53};
    for (int i = 0; i < 12; i++) sc->st[i] = hold[i] < 0 ? 0 : 8 * (full(hold[i]) + 1);
}

}

extern "C" void kernel_launch(void* const* d_in, const int* in_sizes, int n_in, void* d_out, int out_size) {
    (void)in_sizes; (void)n_in; (void)out_size;
    static EncodeFn enc = nullptr;
    static float* scratch = nullptr;
    static bool layout_ok = false;
    if (!enc) {
        void* fn = nullptr;
        cudaDriverEntryPointQueryResult st;
        cudaGetDriverEntryPoint("cuTensorMapEncodeTiled", &fn, cudaEnableDefault, &st);
        enc = (EncodeFn)fn;
        cudaGetSymbolAddress((void**)&scratch, g_scratch);
        cudaFuncSetAttribute(attn_kernel, cudaFuncAttributeMaxDynamicSharedMemorySize, SM_TOTAL);
        int dev = 0, reserved = 0;
        cudaFuncAttributes fa;
        cudaGetDevice(&dev);
        cudaDeviceGetAttribute(&reserved, cudaDevAttrReservedSharedMemoryPerBlock, dev);
        cudaFuncGetAttributes(&fa, attn_kernel);
        layout_ok = enc != nullptr && reserved <= (int)base && fa.sharedSizeBytes == 0;
    }
    if (!layout_ok) {
        generic_kernel<<<128, 480>>>((const __nv_bfloat16*)d_in[0], (const __nv_bfloat16*)d_in[1], (const __nv_bfloat16*)d_in[2],
                                     (const int*)d_in[3], (const int*)d_in[4], (__nv_bfloat16*)d_out);
        return;
    }
    Sched sched;
    make_sched(&sched);
    Maps maps;
    make_map(enc, &maps.q, d_in[0], 64);
    make_map(enc, &maps.k, d_in[1], 64);
    make_map(enc, &maps.v, d_in[2], 64);
    make_map(enc, &maps.o, d_out, 64);
    make_map(enc, &maps.o62, d_out, 64 - FAST_G);
    make_map(enc, &maps.o16, d_out, 16);
    make_map(enc, &maps.k32, d_in[1], 32);
    make_map(enc, &maps.v32, d_in[2], 32);
    attn_kernel<<<128, 480, SM_TOTAL>>>(maps, sched, (const __nv_bfloat16*)d_in[0], (const __nv_bfloat16*)d_in[1],
                                        (const __nv_bfloat16*)d_in[2], (const int*)d_in[3], (const int*)d_in[4],
                                        (__nv_bfloat16*)d_out, scratch);
}
```
